```python
import torch

def _softmax(x, axis=-1):
    return torch.softmax(x, dim=axis)
def _gelu(x):
    return torch.nn.functional.gelu(x, approximate="tanh")
def _silu(x):
    return torch.nn.functional.silu(x)
def _sigmoid(x):
    return torch.sigmoid(x)
def _layernorm(x, axis=-1, eps=1e-5):
    m = x.mean(dim=axis, keepdim=True)
    v = x.var(dim=axis, keepdim=True, unbiased=False)
    return (x - m) / torch.sqrt(v + eps)
def _scatter_add(tgt, idx, src, axis=0):
    return tgt.clone().index_add_(axis, idx, src)
def _segment_sum(src, seg, n):
    out = torch.zeros((n,) + src.shape[1:], dtype=src.dtype)
    return out.index_add_(0, seg, src)
def _pad(x, pw):
    flat = tuple(v for pair in reversed(pw) for v in pair)
    return torch.nn.functional.pad(x, flat)

kernel_name = 'concat_heads__ssm_conv_h3__sliding_local_dilated__prompt'

def setup_inputs():

    _w = (lambda a: (lambda t: t.to(torch.bfloat16) if t.is_floating_point() else t)(torch.as_tensor(a)))
    def _A_setup():
        B, S, D = 1, 2048, 640
        ks = 4
        return {
            "q": _w((lambda *s: torch.randn(*s, dtype=torch.bfloat16) * 0.05)(B, S, D)),
            "k": _w((lambda *s: torch.randn(*s, dtype=torch.bfloat16) * 0.8)(B, S, D)),
            "v": _w((lambda *s: torch.randn(*s, dtype=torch.bfloat16) * 0.8)(B, S, D)),
            "shift_k": _w((lambda *s: torch.randn(*s, dtype=torch.bfloat16) * 0.8)(D, ks) * 0.5),
            "ssm_k": _w((lambda *s: torch.randn(*s, dtype=torch.bfloat16) * 3.2)(D, S) * (1.0 / S ** 0.5)),
            "ssm_D": _w((lambda *s: torch.randn(*s, dtype=torch.bfloat16) * 0.8)(D)),
        }
    _A_in = _A_setup()

    def _B_setup():
        B, S, D = 1, 2048, 640
        return {
            "x": _w((lambda *s: torch.randn(*s, dtype=torch.bfloat16) * 0.2)(B, S, D)),
            "wqkv": _w((lambda *s: torch.randn(*s, dtype=torch.bfloat16) * 0.2)(D, 3 * D)),
            "wo": _w((lambda *s: torch.randn(*s, dtype=torch.bfloat16) * 0.05)(D, D)),
        }
    _B_in = _B_setup()

    return {
        "A_q": _A_in["q"],
        "A_k": _A_in["k"],
        "A_v": _A_in["v"],
        "A_shift_k": _A_in["shift_k"],
        "A_ssm_k": _A_in["ssm_k"],
        "A_ssm_D": _A_in["ssm_D"],
        "B_x": _B_in["x"],
        "B_wqkv": _B_in["wqkv"],
        "B_wo": _B_in["wo"],
    }

def reference(A_q, A_k, A_v, A_shift_k, A_ssm_k, A_ssm_D, B_x, B_wqkv, B_wo):
    def _A_ref(q, k, v, shift_k, ssm_k, ssm_D):
        B, S, D = q.shape
        ks = shift_k.shape[-1]
        k_pad = _pad(k, ((0, 0), (ks - 1, 0), (0, 0)))
        k_shift = torch.zeros_like(k)
        for t in range(ks):
            k_shift = k_shift + k_pad[:, t:t + S, :] * shift_k[:, ks - 1 - t][None, None, :]
        kv = k_shift * v
        L = 2 * S
        kv_pad = _pad(kv, ((0, 0), (0, S), (0, 0)))
        kf_pad = _pad(ssm_k, ((0, 0), (0, S)))
        kv_f = (lambda x, axes=(-2,-1): torch.fft.rfft2(x.float(), dim=axes))(kv_pad[:, None, :, :], axes=(1, 2))
        kf_f = (lambda x, axes=(-2,-1): torch.fft.rfft2(x.float(), dim=axes))(kf_pad[:, None, :], axes=(1, 2))
        kf_f = (lambda x, *d: x.permute(*d))(kf_f, 1, 2, 0)
        y_f = kv_f * kf_f[None, :, :, :]
        y = (lambda x, s, axes=(-2,-1): torch.fft.irfft2(x, s=s, dim=axes).to(torch.bfloat16))(y_f, (1, L), axes=(1, 2))[:, 0, :S, :]
        y = y + kv * ssm_D[None, None, :]
        return q * y

    def _B_ref(x, wqkv, wo):
        B, S, D = x.shape
        H = 32; Dh = D // H
        W, dil = 8, 2
        qkv = (lambda x, *d: x.permute(*d))((x @ wqkv).reshape(B, S, 3, H, Dh), 2, 0, 3, 1, 4)
        q, k, v = qkv[0], qkv[1], qkv[2]
        scale = Dh ** -0.5
        pos = torch.arange(S)
        off = torch.arange(W) * dil
        idx = pos[:, None] - off[None, :]
        mask = idx >= 0
        idx_c = torch.where(mask, idx, 0).reshape(-1)
        kg = k[:, :, idx_c, :].reshape(B, H, S, W, Dh)
        vg = v[:, :, idx_c, :].reshape(B, H, S, W, Dh)
        logits = torch.einsum("bhsd,bhswd->bhsw", q, kg) * scale
        logits = torch.where(mask[None, None, :, :], logits, -1e9)
        attn = _softmax(logits, axis=-1)
        o = torch.einsum("bhsw,bhswd->bhsd", attn, vg)
        return (lambda x, *d: x.permute(*d))(o, 0, 2, 1, 3).reshape(B, S, D) @ wo

    a = _A_ref(A_q, A_k, A_v, A_shift_k, A_ssm_k, A_ssm_D)
    b = _B_ref(B_x, B_wqkv, B_wo)
    return torch.concatenate([a, b], axis=-1)
```

```cpp
#include <cuda_runtime.h>
#include <cuda_bf16.h>
#include <cuda.h>
#include <stdint.h>

typedef __nv_bfloat16 bf16;

__device__ __align__(1024) bf16     g_kvT[640 * 2048];
__device__ __align__(1024) uint32_t g_yT[640 * 1024];
__device__ __align__(1024) bf16     g_o[2048 * 640];
__device__ __align__(1024) uint4    g_halo[128 * 2 * 7 * 32];
__device__ __align__(1024) unsigned g_sync[32 * 8];
#define SY_KV   0
#define SY_Y    32
#define SY_DONE 64
#define SY_O    96
#define SY_EPOCH 128

#define TR(i)
#define TRL(i)
#define TRC(v)
#define TRV(i, v)
#define TRT(i)
#define STAGE_BYTES 47104
#define OFF_W64 16384
#define OFF_W16 40960
#define OFF_S2 (2 * STAGE_BYTES)
#define OFF_S3 (3 * STAGE_BYTES)
#define OFF_KVT (4 * STAGE_BYTES)
#define KVT_PITCH 4128
#define OFF_BAR 231936
#define OFF_PV (OFF_KVT + 23040)
#define OFF_OST 209920
#define SMEM_BYTES 232448

#define NE 2
#define VW 0
#define HW 2
#define B_FULL 0
#define B_EMPTY 4
#define B_KV 8
#define B_OFULL 9
#define B_OEMPTY 19
#define B_QDONE 22
#define B_ATT 23
#define B_AFREE 24
#define B_AREADY 29
#define B_PREP 34
#define B_Y 35
#define B_KVFREE 40
#define B_SFREE 41
#define B_PLOAD 43
#define B_X 44
#define NUM_BARS 43

__device__ __forceinline__ void mbar_init(uint32_t bar, int cnt) { asm volatile("mbarrier.init.shared.b64 [%0], %1;" :: "r"(bar), "r"(cnt) : "memory"); }
__device__ __forceinline__ void mbar_expect(uint32_t bar, uint32_t bytes) { asm volatile("mbarrier.arrive.expect_tx.shared.b64 _, [%0], %1;" :: "r"(bar), "r"(bytes) : "memory"); }
__device__ __forceinline__ void mbar_arrive(uint32_t bar) { asm volatile("mbarrier.arrive.shared.b64 _, [%0];" :: "r"(bar) : "memory"); }
__device__ __forceinline__ uint32_t mbar_try(uint32_t bar, uint32_t ph) {
    uint32_t ok;
    asm volatile("{\n.reg .pred p;\nmbarrier.try_wait.parity.shared.b64 p, [%1], %2;\nselp.u32 %0, 1, 0, p;\n}" : "=r"(ok) : "r"(bar), "r"(ph) : "memory");
    return ok;
}
__device__ __forceinline__ void mbar_wait(uint32_t bar, uint32_t ph) {
    #pragma unroll 1
    for (int it = 0; it < (1 << 18); it++) { if (mbar_try(bar, ph)) return; }
    __trap();
}
__device__ __forceinline__ uint32_t mbar_try_cl(uint32_t bar, uint32_t ph) {
    uint32_t ok;
    asm volatile("{\n.reg .pred p;\nmbarrier.try_wait.parity.shared::cta.b64 p, [%1], %2, %3;\nselp.u32 %0, 1, 0, p;\n}" : "=r"(ok) : "r"(bar), "r"(ph), "r"(20000) : "memory");
    return ok;
}
__device__ __forceinline__ void mbar_wait_cl(uint32_t bar, uint32_t ph) {
    #pragma unroll 1
    for (int it = 0; it < (1 << 20); it++) { if (mbar_try_cl(bar, ph)) return; }
    __trap();
}
__device__ __forceinline__ void mbar_arrive_remote(uint32_t bar, uint32_t cta) {
    asm volatile("{\n.reg .b32 ra;\nmapa.shared::cluster.u32 ra, %0, %1;\nmbarrier.arrive.shared::cluster.b64 _, [ra];\n}" :: "r"(bar), "r"(cta) : "memory");
}
__device__ __forceinline__ unsigned ld_relaxed(const unsigned* p) {
    unsigned v; asm volatile("ld.relaxed.gpu.global.u32 %0, [%1];" : "=r"(v) : "l"(p) : "memory"); return v;
}
__device__ __forceinline__ void poll_ge(const unsigned* p, unsigned target) {
    #pragma unroll 1
    for (int it = 0; it < (1 << 21); it++) {
        if (ld_relaxed(p) >= target) return;
    }
    __trap();
}
__device__ __forceinline__ void red_release(unsigned* p, unsigned v) { asm volatile("red.release.gpu.global.add.u32 [%0], %1;" :: "l"(p), "r"(v) : "memory"); }
__device__ __forceinline__ void red_relaxed(unsigned* p, unsigned v) { asm volatile("red.relaxed.gpu.global.add.u32 [%0], %1;" :: "l"(p), "r"(v) : "memory"); }
__device__ __forceinline__ void fence_async_all() { asm volatile("fence.proxy.async;" ::: "memory"); }
__device__ __forceinline__ void fence_async_smem() { asm volatile("fence.proxy.async.shared::cta;" ::: "memory"); }
__device__ __forceinline__ void bar_sync(int id, int n) { asm volatile("bar.sync %0, %1;" :: "r"(id), "r"(n) : "memory"); }
__device__ __forceinline__ void bar_arrive(int id, int n) { asm volatile("bar.arrive %0, %1;" :: "r"(id), "r"(n) : "memory"); }
__device__ __forceinline__ void tma2d(uint32_t dst, const CUtensorMap* tm, uint32_t bar, int c0, int c1) {
    asm volatile("cp.async.bulk.tensor.2d.shared::cluster.global.mbarrier::complete_tx::bytes [%0], [%1, {%3, %4}], [%2];"
        :: "r"(dst), "l"(tm), "r"(bar), "r"(c0), "r"(c1) : "memory");
}
__device__ __forceinline__ void tma3d(uint32_t dst, const CUtensorMap* tm, uint32_t bar, int c0, int c1, int c2) {
    asm volatile("cp.async.bulk.tensor.3d.shared::cluster.global.mbarrier::complete_tx::bytes [%0], [%1, {%3, %4, %5}], [%2];"
        :: "r"(dst), "l"(tm), "r"(bar), "r"(c0), "r"(c1), "r"(c2) : "memory");
}
__device__ __forceinline__ void tma3d_mc(uint32_t dst, const CUtensorMap* tm, uint32_t bar, int c0, int c1, int c2) {
    asm volatile("cp.async.bulk.tensor.3d.shared::cluster.global.mbarrier::complete_tx::bytes.multicast::cluster [%0], [%1, {%3, %4, %5}], [%2], %6;"
        :: "r"(dst), "l"(tm), "r"(bar), "r"(c0), "r"(c1), "r"(c2), "h"((uint16_t)3) : "memory");
}
__device__ __forceinline__ void tma4d(uint32_t dst, const CUtensorMap* tm, uint32_t bar, int c0, int c3) {
    asm volatile("cp.async.bulk.tensor.4d.shared::cluster.global.mbarrier::complete_tx::bytes [%0], [%1, {%3, %4, %4, %5}], [%2];"
        :: "r"(dst), "l"(tm), "r"(bar), "r"(c0), "r"(0), "r"(c3) : "memory");
}
__device__ __forceinline__ void tma4d_store(const CUtensorMap* tm, uint32_t src, int c0, int c3) {
    asm volatile("cp.async.bulk.tensor.4d.global.shared::cta.bulk_group [%0, {%2, %3, %3, %4}], [%1];" :: "l"(tm), "r"(src), "r"(c0), "r"(0), "r"(c3) : "memory");
}
__device__ __forceinline__ void mma16(float* c, uint32_t a0, uint32_t a1, uint32_t a2, uint32_t a3, uint32_t b0, uint32_t b1) {
    asm("mma.sync.aligned.m16n8k16.row.col.f32.bf16.bf16.f32 {%0,%1,%2,%3}, {%4,%5,%6,%7}, {%8,%9}, {%0,%1,%2,%3};"
        : "+f"(c[0]), "+f"(c[1]), "+f"(c[2]), "+f"(c[3]) : "r"(a0), "r"(a1), "r"(a2), "r"(a3), "r"(b0), "r"(b1));
}
__device__ __forceinline__ void mma8(float* c, uint32_t a0, uint32_t a1, uint32_t b0) {
    asm("mma.sync.aligned.m16n8k8.row.col.f32.bf16.bf16.f32 {%0,%1,%2,%3}, {%4,%5}, {%6}, {%0,%1,%2,%3};"
        : "+f"(c[0]), "+f"(c[1]), "+f"(c[2]), "+f"(c[3]) : "r"(a0), "r"(a1), "r"(b0));
}
__device__ __forceinline__ uint32_t movm(uint32_t a) { uint32_t r; asm("movmatrix.sync.aligned.m8n8.trans.b16 %0, %1;" : "=r"(r) : "r"(a)); return r; }
__device__ __forceinline__ float ex2(float x) { float r; asm("ex2.approx.ftz.f32 %0, %1;" : "=f"(r) : "f"(x)); return r; }
__device__ __forceinline__ uint4 lds128(uint32_t addr) { uint4 v; asm volatile("ld.shared.v4.u32 {%0,%1,%2,%3}, [%4];" : "=r"(v.x), "=r"(v.y), "=r"(v.z), "=r"(v.w) : "r"(addr) : "memory"); return v; }
__device__ __forceinline__ void sts32(uint32_t addr, uint32_t a) { asm volatile("st.shared.u32 [%0], %1;" :: "r"(addr), "r"(a) : "memory"); }
__device__ __forceinline__ uint4 ld_relaxed4(const uint4* p) { uint4 v; asm volatile("ld.relaxed.gpu.global.v4.u32 {%0,%1,%2,%3}, [%4];" : "=r"(v.x), "=r"(v.y), "=r"(v.z), "=r"(v.w) : "l"(p) : "memory"); return v; }
__device__ __forceinline__ void st_relaxed4(uint4* p, uint32_t a, uint32_t b, uint32_t c, uint32_t d) { asm volatile("st.relaxed.gpu.global.v4.u32 [%0], {%1,%2,%3,%4};" :: "l"(p), "r"(a), "r"(b), "r"(c), "r"(d) : "memory"); }
__device__ __forceinline__ void prefetch_tm(const CUtensorMap* tm) { asm volatile("prefetch.tensormap [%0];" :: "l"(tm) : "memory"); }
__device__ __forceinline__ void prefetch_l2(const void* p, uint32_t bytes) { asm volatile("cp.async.bulk.prefetch.L2.global [%0], %1;" :: "l"(p), "r"(bytes) : "memory"); }
__device__ __forceinline__ void tma2d_store(const CUtensorMap* tm, uint32_t src, int c0, int c1) {
    asm volatile("cp.async.bulk.tensor.2d.global.shared::cta.bulk_group [%0, {%2, %3}], [%1];" :: "l"(tm), "r"(src), "r"(c0), "r"(c1) : "memory");
}
__device__ __forceinline__ void tma3d_store(const CUtensorMap* tm, uint32_t src, int c1, int c2) {
    asm volatile("cp.async.bulk.tensor.3d.global.shared::cta.bulk_group [%0, {%2, %3, %4}], [%1];" :: "l"(tm), "r"(src), "r"(0), "r"(c1), "r"(c2) : "memory");
}
__device__ __forceinline__ void bulk_load(uint32_t dst, const void* src, uint32_t bytes, uint32_t bar) {
    asm volatile("cp.async.bulk.shared::cluster.global.mbarrier::complete_tx::bytes [%0], [%1], %2, [%3];" :: "r"(dst), "l"(src), "r"(bytes), "r"(bar) : "memory");
}
__device__ __forceinline__ void bulk_store(void* dst, uint32_t src, uint32_t bytes) {
    asm volatile("cp.async.bulk.global.shared::cta.bulk_group [%0], [%1], %2;" :: "l"(dst), "r"(src), "r"(bytes) : "memory");
}
__device__ __forceinline__ void bulk_commit() { asm volatile("cp.async.bulk.commit_group;" ::: "memory"); }
__device__ __forceinline__ void bulk_wait0() { asm volatile("cp.async.bulk.wait_group 0;" ::: "memory"); }
__device__ __forceinline__ void bulk_wait0_read() { asm volatile("cp.async.bulk.wait_group.read 0;" ::: "memory"); }
__device__ __forceinline__ void stsm4(uint32_t addr, uint32_t a, uint32_t b, uint32_t c, uint32_t d) {
    asm volatile("stmatrix.sync.aligned.m8n8.x4.shared.b16 [%0], {%1, %2, %3, %4};" :: "r"(addr), "r"(a), "r"(b), "r"(c), "r"(d) : "memory");
}
__device__ __forceinline__ void sts128(uint32_t addr, uint32_t a, uint32_t b, uint32_t c, uint32_t d) {
    asm volatile("st.shared.v4.u32 [%0], {%1, %2, %3, %4};" :: "r"(addr), "r"(a), "r"(b), "r"(c), "r"(d) : "memory");
}
__device__ __forceinline__ void sts64f(uint32_t addr, float a, float b) { asm volatile("st.shared.v2.f32 [%0], {%1, %2};" :: "r"(addr), "f"(a), "f"(b) : "memory"); }
__device__ __forceinline__ void sts64(uint32_t addr, uint32_t a, uint32_t b) { asm volatile("st.shared.v2.u32 [%0], {%1, %2};" :: "r"(addr), "r"(a), "r"(b) : "memory"); }
__device__ __forceinline__ float2 lds64f(uint32_t addr) { float2 v; asm volatile("ld.shared.v2.f32 {%0, %1}, [%2];" : "=f"(v.x), "=f"(v.y) : "r"(addr) : "memory"); return v; }
__device__ __forceinline__ uint2 lds64(uint32_t addr) { uint2 v; asm volatile("ld.shared.v2.u32 {%0, %1}, [%2];" : "=r"(v.x), "=r"(v.y) : "r"(addr) : "memory"); return v; }
__device__ __forceinline__ uint32_t pack_bf16(float lo, float hi) { uint32_t r; asm("cvt.rn.bf16x2.f32 %0, %1, %2;" : "=r"(r) : "f"(hi), "f"(lo)); return r; }
__device__ __forceinline__ uint32_t prmt(uint32_t a, uint32_t b, uint32_t sel) { uint32_t r; asm("prmt.b32 %0, %1, %2, %3;" : "=r"(r) : "r"(a), "r"(b), "r"(sel)); return r; }
__device__ __forceinline__ uint32_t hmul2(uint32_t a, uint32_t b) { uint32_t r; asm("mul.rn.bf16x2 %0, %1, %2;" : "=r"(r) : "r"(a), "r"(b)); return r; }
__device__ __forceinline__ uint32_t hadd2(uint32_t a, uint32_t b) { uint32_t r; asm("add.rn.bf16x2 %0, %1, %2;" : "=r"(r) : "r"(a), "r"(b)); return r; }
__device__ __forceinline__ float bflo(uint32_t w) { return __uint_as_float(w << 16); }
__device__ __forceinline__ float bfhi(uint32_t w) { return __uint_as_float(w & 0xffff0000u); }
__device__ __forceinline__ uint4 ldg_nc(const void* p) { uint4 v; asm volatile("ld.global.nc.L1::no_allocate.v4.u32 {%0,%1,%2,%3}, [%4];" : "=r"(v.x), "=r"(v.y), "=r"(v.z), "=r"(v.w) : "l"(p)); return v; }
__device__ __forceinline__ uint4 ldg_ca(const void* p) { uint4 v; asm volatile("ld.global.nc.v4.u32 {%0,%1,%2,%3}, [%4];" : "=r"(v.x), "=r"(v.y), "=r"(v.z), "=r"(v.w) : "l"(p)); return v; }
__device__ __forceinline__ uint4 ldg_cg(const void* p) { uint4 v; asm volatile("ld.global.cg.v4.u32 {%0,%1,%2,%3}, [%4];" : "=r"(v.x), "=r"(v.y), "=r"(v.z), "=r"(v.w) : "l"(p) : "memory"); return v; }

__device__ __forceinline__ uint2 ldg_cg2(const void* p) { uint2 v; asm volatile("ld.global.cg.v2.u32 {%0,%1}, [%2];" : "=r"(v.x), "=r"(v.y) : "l"(p) : "memory"); return v; }
__device__ __forceinline__ void prefetch_l1(const void* p) { asm volatile("prefetch.global.L1 [%0];" :: "l"(p)); }
__device__ __forceinline__ uint32_t sum4(uint32_t a, uint32_t b, uint32_t c, uint32_t d) {
    return pack_bf16((bflo(a) + bflo(b)) + (bflo(c) + bflo(d)), (bfhi(a) + bfhi(b)) + (bfhi(c) + bfhi(d)));
}
__device__ __forceinline__ float rcp(float x) { float r; asm("rcp.approx.ftz.f32 %0, %1;" : "=f"(r) : "f"(x)); return r; }
__device__ __forceinline__ uint32_t hfma2(uint32_t a, uint32_t b, uint32_t c) { uint32_t r; asm("fma.rn.bf16x2 %0, %1, %2, %3;" : "=r"(r) : "r"(a), "r"(b), "r"(c)); return r; }
__device__ __forceinline__ uint32_t lds32(uint32_t addr) { uint32_t v; asm volatile("ld.shared.u32 %0, [%1];" : "=r"(v) : "r"(addr) : "memory"); return v; }
__device__ __forceinline__ void ldsm4(uint32_t* r, uint32_t addr) {
    asm volatile("ldmatrix.sync.aligned.m8n8.x4.shared.b16 {%0, %1, %2, %3}, [%4];" : "=r"(r[0]), "=r"(r[1]), "=r"(r[2]), "=r"(r[3]) : "r"(addr) : "memory");
}
#define WG_FENCE()  asm volatile("wgmma.fence.sync.aligned;" ::: "memory")
#define WG_COMMIT() asm volatile("wgmma.commit_group.sync.aligned;" ::: "memory")
#define WG_WAIT(n)  asm volatile("wgmma.wait_group.sync.aligned " #n ";" ::: "memory")

__device__ __forceinline__ uint64_t mkdesc(uint32_t addr, uint32_t lbo, uint32_t sbo, uint32_t layout) {
    return (uint64_t)((addr & 0x3FFFF) >> 4) | ((uint64_t)(lbo >> 4) << 16) | ((uint64_t)(sbo >> 4) << 32) | ((uint64_t)layout << 62);
}

template<int N, int TB> __device__ __forceinline__ void wgmma_ss(float* d, uint64_t da, uint64_t db, int sc);
template<int N> __device__ __forceinline__ void wgmma_rs(float* d, const uint32_t* a, uint64_t db, int sc);
template<> __device__ __forceinline__ void wgmma_ss<16,0>(float* d, uint64_t da, uint64_t db, int sc) {
  asm volatile("{\n.reg .pred p;\nsetp.ne.b32 p, %10, 0;\nwgmma.mma_async.sync.aligned.m64n16k16.f32.bf16.bf16 {%0,%1,%2,%3,%4,%5,%6,%7}, %8, %9, p, 1, 1, 0, 0;\n}\n" : "+f"(d[0]),"+f"(d[1]),"+f"(d[2]),"+f"(d[3]),"+f"(d[4]),"+f"(d[5]),"+f"(d[6]),"+f"(d[7]) : "l"(da), "l"(db), "r"(sc));
}
template<> __device__ __forceinline__ void wgmma_ss<32,0>(float* d, uint64_t da, uint64_t db, int sc) {
  asm volatile("{\n.reg .pred p;\nsetp.ne.b32 p, %18, 0;\nwgmma.mma_async.sync.aligned.m64n32k16.f32.bf16.bf16 {%0,%1,%2,%3,%4,%5,%6,%7,%8,%9,%10,%11,%12,%13,%14,%15}, %16, %17, p, 1, 1, 0, 0;\n}\n" : "+f"(d[0]),"+f"(d[1]),"+f"(d[2]),"+f"(d[3]),"+f"(d[4]),"+f"(d[5]),"+f"(d[6]),"+f"(d[7]),"+f"(d[8]),"+f"(d[9]),"+f"(d[10]),"+f"(d[11]),"+f"(d[12]),"+f"(d[13]),"+f"(d[14]),"+f"(d[15]) : "l"(da), "l"(db), "r"(sc));
}
template<> __device__ __forceinline__ void wgmma_ss<48,0>(float* d, uint64_t da, uint64_t db, int sc) {
  asm volatile("{\n.reg .pred p;\nsetp.ne.b32 p, %26, 0;\nwgmma.mma_async.sync.aligned.m64n48k16.f32.bf16.bf16 {%0,%1,%2,%3,%4,%5,%6,%7,%8,%9,%10,%11,%12,%13,%14,%15,%16,%17,%18,%19,%20,%21,%22,%23}, %24, %25, p, 1, 1, 0, 0;\n}\n" : "+f"(d[0]),"+f"(d[1]),"+f"(d[2]),"+f"(d[3]),"+f"(d[4]),"+f"(d[5]),"+f"(d[6]),"+f"(d[7]),"+f"(d[8]),"+f"(d[9]),"+f"(d[10]),"+f"(d[11]),"+f"(d[12]),"+f"(d[13]),"+f"(d[14]),"+f"(d[15]),"+f"(d[16]),"+f"(d[17]),"+f"(d[18]),"+f"(d[19]),"+f"(d[20]),"+f"(d[21]),"+f"(d[22]),"+f"(d[23]) : "l"(da), "l"(db), "r"(sc));
}
template<> __device__ __forceinline__ void wgmma_ss<64,0>(float* d, uint64_t da, uint64_t db, int sc) {
  asm volatile("{\n.reg .pred p;\nsetp.ne.b32 p, %34, 0;\nwgmma.mma_async.sync.aligned.m64n64k16.f32.bf16.bf16 {%0,%1,%2,%3,%4,%5,%6,%7,%8,%9,%10,%11,%12,%13,%14,%15,%16,%17,%18,%19,%20,%21,%22,%23,%24,%25,%26,%27,%28,%29,%30,%31}, %32, %33, p, 1, 1, 0, 0;\n}\n" : "+f"(d[0]),"+f"(d[1]),"+f"(d[2]),"+f"(d[3]),"+f"(d[4]),"+f"(d[5]),"+f"(d[6]),"+f"(d[7]),"+f"(d[8]),"+f"(d[9]),"+f"(d[10]),"+f"(d[11]),"+f"(d[12]),"+f"(d[13]),"+f"(d[14]),"+f"(d[15]),"+f"(d[16]),"+f"(d[17]),"+f"(d[18]),"+f"(d[19]),"+f"(d[20]),"+f"(d[21]),"+f"(d[22]),"+f"(d[23]),"+f"(d[24]),"+f"(d[25]),"+f"(d[26]),"+f"(d[27]),"+f"(d[28]),"+f"(d[29]),"+f"(d[30]),"+f"(d[31]) : "l"(da), "l"(db), "r"(sc));
}
template<> __device__ __forceinline__ void wgmma_ss<80,0>(float* d, uint64_t da, uint64_t db, int sc) {
  asm volatile("{\n.reg .pred p;\nsetp.ne.b32 p, %42, 0;\nwgmma.mma_async.sync.aligned.m64n80k16.f32.bf16.bf16 {%0,%1,%2,%3,%4,%5,%6,%7,%8,%9,%10,%11,%12,%13,%14,%15,%16,%17,%18,%19,%20,%21,%22,%23,%24,%25,%26,%27,%28,%29,%30,%31,%32,%33,%34,%35,%36,%37,%38,%39}, %40, %41, p, 1, 1, 0, 0;\n}\n" : "+f"(d[0]),"+f"(d[1]),"+f"(d[2]),"+f"(d[3]),"+f"(d[4]),"+f"(d[5]),"+f"(d[6]),"+f"(d[7]),"+f"(d[8]),"+f"(d[9]),"+f"(d[10]),"+f"(d[11]),"+f"(d[12]),"+f"(d[13]),"+f"(d[14]),"+f"(d[15]),"+f"(d[16]),"+f"(d[17]),"+f"(d[18]),"+f"(d[19]),"+f"(d[20]),"+f"(d[21]),"+f"(d[22]),"+f"(d[23]),"+f"(d[24]),"+f"(d[25]),"+f"(d[26]),"+f"(d[27]),"+f"(d[28]),"+f"(d[29]),"+f"(d[30]),"+f"(d[31]),"+f"(d[32]),"+f"(d[33]),"+f"(d[34]),"+f"(d[35]),"+f"(d[36]),"+f"(d[37]),"+f"(d[38]),"+f"(d[39]) : "l"(da), "l"(db), "r"(sc));
}
template<> __device__ __forceinline__ void wgmma_ss<96,0>(float* d, uint64_t da, uint64_t db, int sc) {
  asm volatile("{\n.reg .pred p;\nsetp.ne.b32 p, %50, 0;\nwgmma.mma_async.sync.aligned.m64n96k16.f32.bf16.bf16 {%0,%1,%2,%3,%4,%5,%6,%7,%8,%9,%10,%11,%12,%13,%14,%15,%16,%17,%18,%19,%20,%21,%22,%23,%24,%25,%26,%27,%28,%29,%30,%31,%32,%33,%34,%35,%36,%37,%38,%39,%40,%41,%42,%43,%44,%45,%46,%47}, %48, %49, p, 1, 1, 0, 0;\n}\n" : "+f"(d[0]),"+f"(d[1]),"+f"(d[2]),"+f"(d[3]),"+f"(d[4]),"+f"(d[5]),"+f"(d[6]),"+f"(d[7]),"+f"(d[8]),"+f"(d[9]),"+f"(d[10]),"+f"(d[11]),"+f"(d[12]),"+f"(d[13]),"+f"(d[14]),"+f"(d[15]),"+f"(d[16]),"+f"(d[17]),"+f"(d[18]),"+f"(d[19]),"+f"(d[20]),"+f"(d[21]),"+f"(d[22]),"+f"(d[23]),"+f"(d[24]),"+f"(d[25]),"+f"(d[26]),"+f"(d[27]),"+f"(d[28]),"+f"(d[29]),"+f"(d[30]),"+f"(d[31]),"+f"(d[32]),"+f"(d[33]),"+f"(d[34]),"+f"(d[35]),"+f"(d[36]),"+f"(d[37]),"+f"(d[38]),"+f"(d[39]),"+f"(d[40]),"+f"(d[41]),"+f"(d[42]),"+f"(d[43]),"+f"(d[44]),"+f"(d[45]),"+f"(d[46]),"+f"(d[47]) : "l"(da), "l"(db), "r"(sc));
}
template<> __device__ __forceinline__ void wgmma_ss<112,0>(float* d, uint64_t da, uint64_t db, int sc) {
  asm volatile("{\n.reg .pred p;\nsetp.ne.b32 p, %58, 0;\nwgmma.mma_async.sync.aligned.m64n112k16.f32.bf16.bf16 {%0,%1,%2,%3,%4,%5,%6,%7,%8,%9,%10,%11,%12,%13,%14,%15,%16,%17,%18,%19,%20,%21,%22,%23,%24,%25,%26,%27,%28,%29,%30,%31,%32,%33,%34,%35,%36,%37,%38,%39,%40,%41,%42,%43,%44,%45,%46,%47,%48,%49,%50,%51,%52,%53,%54,%55}, %56, %57, p, 1, 1, 0, 0;\n}\n" : "+f"(d[0]),"+f"(d[1]),"+f"(d[2]),"+f"(d[3]),"+f"(d[4]),"+f"(d[5]),"+f"(d[6]),"+f"(d[7]),"+f"(d[8]),"+f"(d[9]),"+f"(d[10]),"+f"(d[11]),"+f"(d[12]),"+f"(d[13]),"+f"(d[14]),"+f"(d[15]),"+f"(d[16]),"+f"(d[17]),"+f"(d[18]),"+f"(d[19]),"+f"(d[20]),"+f"(d[21]),"+f"(d[22]),"+f"(d[23]),"+f"(d[24]),"+f"(d[25]),"+f"(d[26]),"+f"(d[27]),"+f"(d[28]),"+f"(d[29]),"+f"(d[30]),"+f"(d[31]),"+f"(d[32]),"+f"(d[33]),"+f"(d[34]),"+f"(d[35]),"+f"(d[36]),"+f"(d[37]),"+f"(d[38]),"+f"(d[39]),"+f"(d[40]),"+f"(d[41]),"+f"(d[42]),"+f"(d[43]),"+f"(d[44]),"+f"(d[45]),"+f"(d[46]),"+f"(d[47]),"+f"(d[48]),"+f"(d[49]),"+f"(d[50]),"+f"(d[51]),"+f"(d[52]),"+f"(d[53]),"+f"(d[54]),"+f"(d[55]) : "l"(da), "l"(db), "r"(sc));
}
template<> __device__ __forceinline__ void wgmma_ss<128,0>(float* d, uint64_t da, uint64_t db, int sc) {
  asm volatile("{\n.reg .pred p;\nsetp.ne.b32 p, %66, 0;\nwgmma.mma_async.sync.aligned.m64n128k16.f32.bf16.bf16 {%0,%1,%2,%3,%4,%5,%6,%7,%8,%9,%10,%11,%12,%13,%14,%15,%16,%17,%18,%19,%20,%21,%22,%23,%24,%25,%26,%27,%28,%29,%30,%31,%32,%33,%34,%35,%36,%37,%38,%39,%40,%41,%42,%43,%44,%45,%46,%47,%48,%49,%50,%51,%52,%53,%54,%55,%56,%57,%58,%59,%60,%61,%62,%63}, %64, %65, p, 1, 1, 0, 0;\n}\n" : "+f"(d[0]),"+f"(d[1]),"+f"(d[2]),"+f"(d[3]),"+f"(d[4]),"+f"(d[5]),"+f"(d[6]),"+f"(d[7]),"+f"(d[8]),"+f"(d[9]),"+f"(d[10]),"+f"(d[11]),"+f"(d[12]),"+f"(d[13]),"+f"(d[14]),"+f"(d[15]),"+f"(d[16]),"+f"(d[17]),"+f"(d[18]),"+f"(d[19]),"+f"(d[20]),"+f"(d[21]),"+f"(d[22]),"+f"(d[23]),"+f"(d[24]),"+f"(d[25]),"+f"(d[26]),"+f"(d[27]),"+f"(d[28]),"+f"(d[29]),"+f"(d[30]),"+f"(d[31]),"+f"(d[32]),"+f"(d[33]),"+f"(d[34]),"+f"(d[35]),"+f"(d[36]),"+f"(d[37]),"+f"(d[38]),"+f"(d[39]),"+f"(d[40]),"+f"(d[41]),"+f"(d[42]),"+f"(d[43]),"+f"(d[44]),"+f"(d[45]),"+f"(d[46]),"+f"(d[47]),"+f"(d[48]),"+f"(d[49]),"+f"(d[50]),"+f"(d[51]),"+f"(d[52]),"+f"(d[53]),"+f"(d[54]),"+f"(d[55]),"+f"(d[56]),"+f"(d[57]),"+f"(d[58]),"+f"(d[59]),"+f"(d[60]),"+f"(d[61]),"+f"(d[62]),"+f"(d[63]) : "l"(da), "l"(db), "r"(sc));
}
template<> __device__ __forceinline__ void wgmma_ss<144,0>(float* d, uint64_t da, uint64_t db, int sc) {
  asm volatile("{\n.reg .pred p;\nsetp.ne.b32 p, %74, 0;\nwgmma.mma_async.sync.aligned.m64n144k16.f32.bf16.bf16 {%0,%1,%2,%3,%4,%5,%6,%7,%8,%9,%10,%11,%12,%13,%14,%15,%16,%17,%18,%19,%20,%21,%22,%23,%24,%25,%26,%27,%28,%29,%30,%31,%32,%33,%34,%35,%36,%37,%38,%39,%40,%41,%42,%43,%44,%45,%46,%47,%48,%49,%50,%51,%52,%53,%54,%55,%56,%57,%58,%59,%60,%61,%62,%63,%64,%65,%66,%67,%68,%69,%70,%71}, %72, %73, p, 1, 1, 0, 0;\n}\n" : "+f"(d[0]),"+f"(d[1]),"+f"(d[2]),"+f"(d[3]),"+f"(d[4]),"+f"(d[5]),"+f"(d[6]),"+f"(d[7]),"+f"(d[8]),"+f"(d[9]),"+f"(d[10]),"+f"(d[11]),"+f"(d[12]),"+f"(d[13]),"+f"(d[14]),"+f"(d[15]),"+f"(d[16]),"+f"(d[17]),"+f"(d[18]),"+f"(d[19]),"+f"(d[20]),"+f"(d[21]),"+f"(d[22]),"+f"(d[23]),"+f"(d[24]),"+f"(d[25]),"+f"(d[26]),"+f"(d[27]),"+f"(d[28]),"+f"(d[29]),"+f"(d[30]),"+f"(d[31]),"+f"(d[32]),"+f"(d[33]),"+f"(d[34]),"+f"(d[35]),"+f"(d[36]),"+f"(d[37]),"+f"(d[38]),"+f"(d[39]),"+f"(d[40]),"+f"(d[41]),"+f"(d[42]),"+f"(d[43]),"+f"(d[44]),"+f"(d[45]),"+f"(d[46]),"+f"(d[47]),"+f"(d[48]),"+f"(d[49]),"+f"(d[50]),"+f"(d[51]),"+f"(d[52]),"+f"(d[53]),"+f"(d[54]),"+f"(d[55]),"+f"(d[56]),"+f"(d[57]),"+f"(d[58]),"+f"(d[59]),"+f"(d[60]),"+f"(d[61]),"+f"(d[62]),"+f"(d[63]),"+f"(d[64]),"+f"(d[65]),"+f"(d[66]),"+f"(d[67]),"+f"(d[68]),"+f"(d[69]),"+f"(d[70]),"+f"(d[71]) : "l"(da), "l"(db), "r"(sc));
}
template<> __device__ __forceinline__ void wgmma_ss<160,0>(float* d, uint64_t da, uint64_t db, int sc) {
  asm volatile("{\n.reg .pred p;\nsetp.ne.b32 p, %82, 0;\nwgmma.mma_async.sync.aligned.m64n160k16.f32.bf16.bf16 {%0,%1,%2,%3,%4,%5,%6,%7,%8,%9,%10,%11,%12,%13,%14,%15,%16,%17,%18,%19,%20,%21,%22,%23,%24,%25,%26,%27,%28,%29,%30,%31,%32,%33,%34,%35,%36,%37,%38,%39,%40,%41,%42,%43,%44,%45,%46,%47,%48,%49,%50,%51,%52,%53,%54,%55,%56,%57,%58,%59,%60,%61,%62,%63,%64,%65,%66,%67,%68,%69,%70,%71,%72,%73,%74,%75,%76,%77,%78,%79}, %80, %81, p, 1, 1, 0, 0;\n}\n" : "+f"(d[0]),"+f"(d[1]),"+f"(d[2]),"+f"(d[3]),"+f"(d[4]),"+f"(d[5]),"+f"(d[6]),"+f"(d[7]),"+f"(d[8]),"+f"(d[9]),"+f"(d[10]),"+f"(d[11]),"+f"(d[12]),"+f"(d[13]),"+f"(d[14]),"+f"(d[15]),"+f"(d[16]),"+f"(d[17]),"+f"(d[18]),"+f"(d[19]),"+f"(d[20]),"+f"(d[21]),"+f"(d[22]),"+f"(d[23]),"+f"(d[24]),"+f"(d[25]),"+f"(d[26]),"+f"(d[27]),"+f"(d[28]),"+f"(d[29]),"+f"(d[30]),"+f"(d[31]),"+f"(d[32]),"+f"(d[33]),"+f"(d[34]),"+f"(d[35]),"+f"(d[36]),"+f"(d[37]),"+f"(d[38]),"+f"(d[39]),"+f"(d[40]),"+f"(d[41]),"+f"(d[42]),"+f"(d[43]),"+f"(d[44]),"+f"(d[45]),"+f"(d[46]),"+f"(d[47]),"+f"(d[48]),"+f"(d[49]),"+f"(d[50]),"+f"(d[51]),"+f"(d[52]),"+f"(d[53]),"+f"(d[54]),"+f"(d[55]),"+f"(d[56]),"+f"(d[57]),"+f"(d[58]),"+f"(d[59]),"+f"(d[60]),"+f"(d[61]),"+f"(d[62]),"+f"(d[63]),"+f"(d[64]),"+f"(d[65]),"+f"(d[66]),"+f"(d[67]),"+f"(d[68]),"+f"(d[69]),"+f"(d[70]),"+f"(d[71]),"+f"(d[72]),"+f"(d[73]),"+f"(d[74]),"+f"(d[75]),"+f"(d[76]),"+f"(d[77]),"+f"(d[78]),"+f"(d[79]) : "l"(da), "l"(db), "r"(sc));
}
template<> __device__ __forceinline__ void wgmma_ss<176,0>(float* d, uint64_t da, uint64_t db, int sc) {
  asm volatile("{\n.reg .pred p;\nsetp.ne.b32 p, %90, 0;\nwgmma.mma_async.sync.aligned.m64n176k16.f32.bf16.bf16 {%0,%1,%2,%3,%4,%5,%6,%7,%8,%9,%10,%11,%12,%13,%14,%15,%16,%17,%18,%19,%20,%21,%22,%23,%24,%25,%26,%27,%28,%29,%30,%31,%32,%33,%34,%35,%36,%37,%38,%39,%40,%41,%42,%43,%44,%45,%46,%47,%48,%49,%50,%51,%52,%53,%54,%55,%56,%57,%58,%59,%60,%61,%62,%63,%64,%65,%66,%67,%68,%69,%70,%71,%72,%73,%74,%75,%76,%77,%78,%79,%80,%81,%82,%83,%84,%85,%86,%87}, %88, %89, p, 1, 1, 0, 0;\n}\n" : "+f"(d[0]),"+f"(d[1]),"+f"(d[2]),"+f"(d[3]),"+f"(d[4]),"+f"(d[5]),"+f"(d[6]),"+f"(d[7]),"+f"(d[8]),"+f"(d[9]),"+f"(d[10]),"+f"(d[11]),"+f"(d[12]),"+f"(d[13]),"+f"(d[14]),"+f"(d[15]),"+f"(d[16]),"+f"(d[17]),"+f"(d[18]),"+f"(d[19]),"+f"(d[20]),"+f"(d[21]),"+f"(d[22]),"+f"(d[23]),"+f"(d[24]),"+f"(d[25]),"+f"(d[26]),"+f"(d[27]),"+f"(d[28]),"+f"(d[29]),"+f"(d[30]),"+f"(d[31]),"+f"(d[32]),"+f"(d[33]),"+f"(d[34]),"+f"(d[35]),"+f"(d[36]),"+f"(d[37]),"+f"(d[38]),"+f"(d[39]),"+f"(d[40]),"+f"(d[41]),"+f"(d[42]),"+f"(d[43]),"+f"(d[44]),"+f"(d[45]),"+f"(d[46]),"+f"(d[47]),"+f"(d[48]),"+f"(d[49]),"+f"(d[50]),"+f"(d[51]),"+f"(d[52]),"+f"(d[53]),"+f"(d[54]),"+f"(d[55]),"+f"(d[56]),"+f"(d[57]),"+f"(d[58]),"+f"(d[59]),"+f"(d[60]),"+f"(d[61]),"+f"(d[62]),"+f"(d[63]),"+f"(d[64]),"+f"(d[65]),"+f"(d[66]),"+f"(d[67]),"+f"(d[68]),"+f"(d[69]),"+f"(d[70]),"+f"(d[71]),"+f"(d[72]),"+f"(d[73]),"+f"(d[74]),"+f"(d[75]),"+f"(d[76]),"+f"(d[77]),"+f"(d[78]),"+f"(d[79]),"+f"(d[80]),"+f"(d[81]),"+f"(d[82]),"+f"(d[83]),"+f"(d[84]),"+f"(d[85]),"+f"(d[86]),"+f"(d[87]) : "l"(da), "l"(db), "r"(sc));
}
template<> __device__ __forceinline__ void wgmma_ss<192,0>(float* d, uint64_t da, uint64_t db, int sc) {
  asm volatile("{\n.reg .pred p;\nsetp.ne.b32 p, %98, 0;\nwgmma.mma_async.sync.aligned.m64n192k16.f32.bf16.bf16 {%0,%1,%2,%3,%4,%5,%6,%7,%8,%9,%10,%11,%12,%13,%14,%15,%16,%17,%18,%19,%20,%21,%22,%23,%24,%25,%26,%27,%28,%29,%30,%31,%32,%33,%34,%35,%36,%37,%38,%39,%40,%41,%42,%43,%44,%45,%46,%47,%48,%49,%50,%51,%52,%53,%54,%55,%56,%57,%58,%59,%60,%61,%62,%63,%64,%65,%66,%67,%68,%69,%70,%71,%72,%73,%74,%75,%76,%77,%78,%79,%80,%81,%82,%83,%84,%85,%86,%87,%88,%89,%90,%91,%92,%93,%94,%95}, %96, %97, p, 1, 1, 0, 0;\n}\n" : "+f"(d[0]),"+f"(d[1]),"+f"(d[2]),"+f"(d[3]),"+f"(d[4]),"+f"(d[5]),"+f"(d[6]),"+f"(d[7]),"+f"(d[8]),"+f"(d[9]),"+f"(d[10]),"+f"(d[11]),"+f"(d[12]),"+f"(d[13]),"+f"(d[14]),"+f"(d[15]),"+f"(d[16]),"+f"(d[17]),"+f"(d[18]),"+f"(d[19]),"+f"(d[20]),"+f"(d[21]),"+f"(d[22]),"+f"(d[23]),"+f"(d[24]),"+f"(d[25]),"+f"(d[26]),"+f"(d[27]),"+f"(d[28]),"+f"(d[29]),"+f"(d[30]),"+f"(d[31]),"+f"(d[32]),"+f"(d[33]),"+f"(d[34]),"+f"(d[35]),"+f"(d[36]),"+f"(d[37]),"+f"(d[38]),"+f"(d[39]),"+f"(d[40]),"+f"(d[41]),"+f"(d[42]),"+f"(d[43]),"+f"(d[44]),"+f"(d[45]),"+f"(d[46]),"+f"(d[47]),"+f"(d[48]),"+f"(d[49]),"+f"(d[50]),"+f"(d[51]),"+f"(d[52]),"+f"(d[53]),"+f"(d[54]),"+f"(d[55]),"+f"(d[56]),"+f"(d[57]),"+f"(d[58]),"+f"(d[59]),"+f"(d[60]),"+f"(d[61]),"+f"(d[62]),"+f"(d[63]),"+f"(d[64]),"+f"(d[65]),"+f"(d[66]),"+f"(d[67]),"+f"(d[68]),"+f"(d[69]),"+f"(d[70]),"+f"(d[71]),"+f"(d[72]),"+f"(d[73]),"+f"(d[74]),"+f"(d[75]),"+f"(d[76]),"+f"(d[77]),"+f"(d[78]),"+f"(d[79]),"+f"(d[80]),"+f"(d[81]),"+f"(d[82]),"+f"(d[83]),"+f"(d[84]),"+f"(d[85]),"+f"(d[86]),"+f"(d[87]),"+f"(d[88]),"+f"(d[89]),"+f"(d[90]),"+f"(d[91]),"+f"(d[92]),"+f"(d[93]),"+f"(d[94]),"+f"(d[95]) : "l"(da), "l"(db), "r"(sc));
}
template<> __device__ __forceinline__ void wgmma_ss<192,1>(float* d, uint64_t da, uint64_t db, int sc) {
  asm volatile("{\n.reg .pred p;\nsetp.ne.b32 p, %98, 0;\nwgmma.mma_async.sync.aligned.m64n192k16.f32.bf16.bf16 {%0,%1,%2,%3,%4,%5,%6,%7,%8,%9,%10,%11,%12,%13,%14,%15,%16,%17,%18,%19,%20,%21,%22,%23,%24,%25,%26,%27,%28,%29,%30,%31,%32,%33,%34,%35,%36,%37,%38,%39,%40,%41,%42,%43,%44,%45,%46,%47,%48,%49,%50,%51,%52,%53,%54,%55,%56,%57,%58,%59,%60,%61,%62,%63,%64,%65,%66,%67,%68,%69,%70,%71,%72,%73,%74,%75,%76,%77,%78,%79,%80,%81,%82,%83,%84,%85,%86,%87,%88,%89,%90,%91,%92,%93,%94,%95}, %96, %97, p, 1, 1, 0, 1;\n}\n" : "+f"(d[0]),"+f"(d[1]),"+f"(d[2]),"+f"(d[3]),"+f"(d[4]),"+f"(d[5]),"+f"(d[6]),"+f"(d[7]),"+f"(d[8]),"+f"(d[9]),"+f"(d[10]),"+f"(d[11]),"+f"(d[12]),"+f"(d[13]),"+f"(d[14]),"+f"(d[15]),"+f"(d[16]),"+f"(d[17]),"+f"(d[18]),"+f"(d[19]),"+f"(d[20]),"+f"(d[21]),"+f"(d[22]),"+f"(d[23]),"+f"(d[24]),"+f"(d[25]),"+f"(d[26]),"+f"(d[27]),"+f"(d[28]),"+f"(d[29]),"+f"(d[30]),"+f"(d[31]),"+f"(d[32]),"+f"(d[33]),"+f"(d[34]),"+f"(d[35]),"+f"(d[36]),"+f"(d[37]),"+f"(d[38]),"+f"(d[39]),"+f"(d[40]),"+f"(d[41]),"+f"(d[42]),"+f"(d[43]),"+f"(d[44]),"+f"(d[45]),"+f"(d[46]),"+f"(d[47]),"+f"(d[48]),"+f"(d[49]),"+f"(d[50]),"+f"(d[51]),"+f"(d[52]),"+f"(d[53]),"+f"(d[54]),"+f"(d[55]),"+f"(d[56]),"+f"(d[57]),"+f"(d[58]),"+f"(d[59]),"+f"(d[60]),"+f"(d[61]),"+f"(d[62]),"+f"(d[63]),"+f"(d[64]),"+f"(d[65]),"+f"(d[66]),"+f"(d[67]),"+f"(d[68]),"+f"(d[69]),"+f"(d[70]),"+f"(d[71]),"+f"(d[72]),"+f"(d[73]),"+f"(d[74]),"+f"(d[75]),"+f"(d[76]),"+f"(d[77]),"+f"(d[78]),"+f"(d[79]),"+f"(d[80]),"+f"(d[81]),"+f"(d[82]),"+f"(d[83]),"+f"(d[84]),"+f"(d[85]),"+f"(d[86]),"+f"(d[87]),"+f"(d[88]),"+f"(d[89]),"+f"(d[90]),"+f"(d[91]),"+f"(d[92]),"+f"(d[93]),"+f"(d[94]),"+f"(d[95]) : "l"(da), "l"(db), "r"(sc));
}
template<> __device__ __forceinline__ void wgmma_ss<48,1>(float* d, uint64_t da, uint64_t db, int sc) {
  asm volatile("{\n.reg .pred p;\nsetp.ne.b32 p, %26, 0;\nwgmma.mma_async.sync.aligned.m64n48k16.f32.bf16.bf16 {%0,%1,%2,%3,%4,%5,%6,%7,%8,%9,%10,%11,%12,%13,%14,%15,%16,%17,%18,%19,%20,%21,%22,%23}, %24, %25, p, 1, 1, 0, 1;\n}\n" : "+f"(d[0]),"+f"(d[1]),"+f"(d[2]),"+f"(d[3]),"+f"(d[4]),"+f"(d[5]),"+f"(d[6]),"+f"(d[7]),"+f"(d[8]),"+f"(d[9]),"+f"(d[10]),"+f"(d[11]),"+f"(d[12]),"+f"(d[13]),"+f"(d[14]),"+f"(d[15]),"+f"(d[16]),"+f"(d[17]),"+f"(d[18]),"+f"(d[19]),"+f"(d[20]),"+f"(d[21]),"+f"(d[22]),"+f"(d[23]) : "l"(da), "l"(db), "r"(sc));
}
template<> __device__ __forceinline__ void wgmma_ss<160,1>(float* d, uint64_t da, uint64_t db, int sc) {
  asm volatile("{\n.reg .pred p;\nsetp.ne.b32 p, %82, 0;\nwgmma.mma_async.sync.aligned.m64n160k16.f32.bf16.bf16 {%0,%1,%2,%3,%4,%5,%6,%7,%8,%9,%10,%11,%12,%13,%14,%15,%16,%17,%18,%19,%20,%21,%22,%23,%24,%25,%26,%27,%28,%29,%30,%31,%32,%33,%34,%35,%36,%37,%38,%39,%40,%41,%42,%43,%44,%45,%46,%47,%48,%49,%50,%51,%52,%53,%54,%55,%56,%57,%58,%59,%60,%61,%62,%63,%64,%65,%66,%67,%68,%69,%70,%71,%72,%73,%74,%75,%76,%77,%78,%79}, %80, %81, p, 1, 1, 0, 1;\n}\n" : "+f"(d[0]),"+f"(d[1]),"+f"(d[2]),"+f"(d[3]),"+f"(d[4]),"+f"(d[5]),"+f"(d[6]),"+f"(d[7]),"+f"(d[8]),"+f"(d[9]),"+f"(d[10]),"+f"(d[11]),"+f"(d[12]),"+f"(d[13]),"+f"(d[14]),"+f"(d[15]),"+f"(d[16]),"+f"(d[17]),"+f"(d[18]),"+f"(d[19]),"+f"(d[20]),"+f"(d[21]),"+f"(d[22]),"+f"(d[23]),"+f"(d[24]),"+f"(d[25]),"+f"(d[26]),"+f"(d[27]),"+f"(d[28]),"+f"(d[29]),"+f"(d[30]),"+f"(d[31]),"+f"(d[32]),"+f"(d[33]),"+f"(d[34]),"+f"(d[35]),"+f"(d[36]),"+f"(d[37]),"+f"(d[38]),"+f"(d[39]),"+f"(d[40]),"+f"(d[41]),"+f"(d[42]),"+f"(d[43]),"+f"(d[44]),"+f"(d[45]),"+f"(d[46]),"+f"(d[47]),"+f"(d[48]),"+f"(d[49]),"+f"(d[50]),"+f"(d[51]),"+f"(d[52]),"+f"(d[53]),"+f"(d[54]),"+f"(d[55]),"+f"(d[56]),"+f"(d[57]),"+f"(d[58]),"+f"(d[59]),"+f"(d[60]),"+f"(d[61]),"+f"(d[62]),"+f"(d[63]),"+f"(d[64]),"+f"(d[65]),"+f"(d[66]),"+f"(d[67]),"+f"(d[68]),"+f"(d[69]),"+f"(d[70]),"+f"(d[71]),"+f"(d[72]),"+f"(d[73]),"+f"(d[74]),"+f"(d[75]),"+f"(d[76]),"+f"(d[77]),"+f"(d[78]),"+f"(d[79]) : "l"(da), "l"(db), "r"(sc));
}
template<> __device__ __forceinline__ void wgmma_ss<96,1>(float* d, uint64_t da, uint64_t db, int sc) {
  asm volatile("{\n.reg .pred p;\nsetp.ne.b32 p, %50, 0;\nwgmma.mma_async.sync.aligned.m64n96k16.f32.bf16.bf16 {%0,%1,%2,%3,%4,%5,%6,%7,%8,%9,%10,%11,%12,%13,%14,%15,%16,%17,%18,%19,%20,%21,%22,%23,%24,%25,%26,%27,%28,%29,%30,%31,%32,%33,%34,%35,%36,%37,%38,%39,%40,%41,%42,%43,%44,%45,%46,%47}, %48, %49, p, 1, 1, 0, 1;\n}\n" : "+f"(d[0]),"+f"(d[1]),"+f"(d[2]),"+f"(d[3]),"+f"(d[4]),"+f"(d[5]),"+f"(d[6]),"+f"(d[7]),"+f"(d[8]),"+f"(d[9]),"+f"(d[10]),"+f"(d[11]),"+f"(d[12]),"+f"(d[13]),"+f"(d[14]),"+f"(d[15]),"+f"(d[16]),"+f"(d[17]),"+f"(d[18]),"+f"(d[19]),"+f"(d[20]),"+f"(d[21]),"+f"(d[22]),"+f"(d[23]),"+f"(d[24]),"+f"(d[25]),"+f"(d[26]),"+f"(d[27]),"+f"(d[28]),"+f"(d[29]),"+f"(d[30]),"+f"(d[31]),"+f"(d[32]),"+f"(d[33]),"+f"(d[34]),"+f"(d[35]),"+f"(d[36]),"+f"(d[37]),"+f"(d[38]),"+f"(d[39]),"+f"(d[40]),"+f"(d[41]),"+f"(d[42]),"+f"(d[43]),"+f"(d[44]),"+f"(d[45]),"+f"(d[46]),"+f"(d[47]) : "l"(da), "l"(db), "r"(sc));
}
template<> __device__ __forceinline__ void wgmma_ss<64,1>(float* d, uint64_t da, uint64_t db, int sc) {
  asm volatile("{\n.reg .pred p;\nsetp.ne.b32 p, %34, 0;\nwgmma.mma_async.sync.aligned.m64n64k16.f32.bf16.bf16 {%0,%1,%2,%3,%4,%5,%6,%7,%8,%9,%10,%11,%12,%13,%14,%15,%16,%17,%18,%19,%20,%21,%22,%23,%24,%25,%26,%27,%28,%29,%30,%31}, %32, %33, p, 1, 1, 0, 1;\n}\n" : "+f"(d[0]),"+f"(d[1]),"+f"(d[2]),"+f"(d[3]),"+f"(d[4]),"+f"(d[5]),"+f"(d[6]),"+f"(d[7]),"+f"(d[8]),"+f"(d[9]),"+f"(d[10]),"+f"(d[11]),"+f"(d[12]),"+f"(d[13]),"+f"(d[14]),"+f"(d[15]),"+f"(d[16]),"+f"(d[17]),"+f"(d[18]),"+f"(d[19]),"+f"(d[20]),"+f"(d[21]),"+f"(d[22]),"+f"(d[23]),"+f"(d[24]),"+f"(d[25]),"+f"(d[26]),"+f"(d[27]),"+f"(d[28]),"+f"(d[29]),"+f"(d[30]),"+f"(d[31]) : "l"(da), "l"(db), "r"(sc));
}
template<> __device__ __forceinline__ void wgmma_rs<192>(float* d, const uint32_t* a, uint64_t db, int sc) {
  asm volatile("{\n.reg .pred p;\nsetp.ne.b32 p, %101, 0;\nwgmma.mma_async.sync.aligned.m64n192k16.f32.bf16.bf16 {%0,%1,%2,%3,%4,%5,%6,%7,%8,%9,%10,%11,%12,%13,%14,%15,%16,%17,%18,%19,%20,%21,%22,%23,%24,%25,%26,%27,%28,%29,%30,%31,%32,%33,%34,%35,%36,%37,%38,%39,%40,%41,%42,%43,%44,%45,%46,%47,%48,%49,%50,%51,%52,%53,%54,%55,%56,%57,%58,%59,%60,%61,%62,%63,%64,%65,%66,%67,%68,%69,%70,%71,%72,%73,%74,%75,%76,%77,%78,%79,%80,%81,%82,%83,%84,%85,%86,%87,%88,%89,%90,%91,%92,%93,%94,%95}, {%96,%97,%98,%99}, %100, p, 1, 1, 1;\n}\n" : "+f"(d[0]),"+f"(d[1]),"+f"(d[2]),"+f"(d[3]),"+f"(d[4]),"+f"(d[5]),"+f"(d[6]),"+f"(d[7]),"+f"(d[8]),"+f"(d[9]),"+f"(d[10]),"+f"(d[11]),"+f"(d[12]),"+f"(d[13]),"+f"(d[14]),"+f"(d[15]),"+f"(d[16]),"+f"(d[17]),"+f"(d[18]),"+f"(d[19]),"+f"(d[20]),"+f"(d[21]),"+f"(d[22]),"+f"(d[23]),"+f"(d[24]),"+f"(d[25]),"+f"(d[26]),"+f"(d[27]),"+f"(d[28]),"+f"(d[29]),"+f"(d[30]),"+f"(d[31]),"+f"(d[32]),"+f"(d[33]),"+f"(d[34]),"+f"(d[35]),"+f"(d[36]),"+f"(d[37]),"+f"(d[38]),"+f"(d[39]),"+f"(d[40]),"+f"(d[41]),"+f"(d[42]),"+f"(d[43]),"+f"(d[44]),"+f"(d[45]),"+f"(d[46]),"+f"(d[47]),"+f"(d[48]),"+f"(d[49]),"+f"(d[50]),"+f"(d[51]),"+f"(d[52]),"+f"(d[53]),"+f"(d[54]),"+f"(d[55]),"+f"(d[56]),"+f"(d[57]),"+f"(d[58]),"+f"(d[59]),"+f"(d[60]),"+f"(d[61]),"+f"(d[62]),"+f"(d[63]),"+f"(d[64]),"+f"(d[65]),"+f"(d[66]),"+f"(d[67]),"+f"(d[68]),"+f"(d[69]),"+f"(d[70]),"+f"(d[71]),"+f"(d[72]),"+f"(d[73]),"+f"(d[74]),"+f"(d[75]),"+f"(d[76]),"+f"(d[77]),"+f"(d[78]),"+f"(d[79]),"+f"(d[80]),"+f"(d[81]),"+f"(d[82]),"+f"(d[83]),"+f"(d[84]),"+f"(d[85]),"+f"(d[86]),"+f"(d[87]),"+f"(d[88]),"+f"(d[89]),"+f"(d[90]),"+f"(d[91]),"+f"(d[92]),"+f"(d[93]),"+f"(d[94]),"+f"(d[95]) : "r"(a[0]), "r"(a[1]), "r"(a[2]), "r"(a[3]), "l"(db), "r"(sc));
}
template<> __device__ __forceinline__ void wgmma_rs<48>(float* d, const uint32_t* a, uint64_t db, int sc) {
  asm volatile("{\n.reg .pred p;\nsetp.ne.b32 p, %29, 0;\nwgmma.mma_async.sync.aligned.m64n48k16.f32.bf16.bf16 {%0,%1,%2,%3,%4,%5,%6,%7,%8,%9,%10,%11,%12,%13,%14,%15,%16,%17,%18,%19,%20,%21,%22,%23}, {%24,%25,%26,%27}, %28, p, 1, 1, 1;\n}\n" : "+f"(d[0]),"+f"(d[1]),"+f"(d[2]),"+f"(d[3]),"+f"(d[4]),"+f"(d[5]),"+f"(d[6]),"+f"(d[7]),"+f"(d[8]),"+f"(d[9]),"+f"(d[10]),"+f"(d[11]),"+f"(d[12]),"+f"(d[13]),"+f"(d[14]),"+f"(d[15]),"+f"(d[16]),"+f"(d[17]),"+f"(d[18]),"+f"(d[19]),"+f"(d[20]),"+f"(d[21]),"+f"(d[22]),"+f"(d[23]) : "r"(a[0]), "r"(a[1]), "r"(a[2]), "r"(a[3]), "l"(db), "r"(sc));
}

template<int Q> __device__ __forceinline__ void conv_steps(float* lo, float* hi, uint64_t da, uint64_t db) {
    constexpr int N = 256 - 16 * Q;
    const uint64_t a = da + (uint64_t)(((Q / 4) * 8192 + (Q % 4) * 32) >> 4), b = db + (uint64_t)((Q * 256) >> 4);
    if constexpr (N > 192) {
        wgmma_ss<192, 0>(lo, a, b, Q != 0);
        wgmma_ss<N - 192, 0>(hi, a, b + (uint64_t)(3072 >> 4), Q != 0);
    } else {
        wgmma_ss<N, 0>(lo, a, b, 1);
    }
}

struct Params {
    const bf16 *q, *k, *v, *shift_k, *ssm_k, *ssm_D, *x, *wqkv, *wo;
    bf16* out;
};
struct HRegs { uint4 p[2], c[2]; uint32_t d; };
__device__ __forceinline__ void h_load(HRegs& r, const Params& P, int ch, int t) {
    const bf16* hch = P.ssm_k + (size_t)ch * 2048;
    r.d = __bfloat16_as_ushort(P.ssm_D[ch]);
    int cidx = t & 7, mu = ((t >> 3) & 3) * 2 + ((t >> 5) & 1);
    #pragma unroll
    for (int i = 0; i < 2; i++) {
        int tile = (t >> 6) + 2 * i;
        int q = tile * 4 + (cidx >> 1);
        int u = 2 * (mu >> 1) + 8 * (mu & 1) + (cidx & 1) + 16 * q;
        r.c[i] = ldg_ca(hch + 8 * u);
        r.p[i] = ldg_ca(hch + (u > 0 ? 8 * u - 8 : 0));
    }
}
__device__ __forceinline__ void h_expand(const HRegs& r, uint32_t abuf, int t) {
    int cidx = t & 7, mu = ((t >> 3) & 3) * 2 + ((t >> 5) & 1);
    #pragma unroll
    for (int i = 0; i < 2; i++) {
        int tile = (t >> 6) + 2 * i;
        uint32_t base = abuf + tile * 8192 + mu * 1024;
        uint32_t w[8] = {r.p[i].x, r.p[i].y, r.p[i].z, r.p[i].w, r.c[i].x, r.c[i].y, r.c[i].z, r.c[i].w};
        if (i == 0 && t == 0) { w[0] = 0; w[1] = 0; w[2] = 0; w[3] = 0; w[4] = hadd2(w[4], r.d); }
        if (i == 0 && t == 1) w[0] = hadd2(w[0], r.d);
        uint32_t o[7];
        #pragma unroll
        for (int k = 0; k < 7; k++) o[k] = prmt(w[k], w[k + 1], 0x5432);
        #pragma unroll
        for (int g = 0; g < 8; g++) {
            uint32_t a = base + g * 128 + ((cidx ^ g) << 4);
            if (g & 1) { int k = (g + 1) >> 1; sts128(a, w[k], w[k + 1], w[k + 2], w[k + 3]); }
            else       { int k = g >> 1;       sts128(a, o[k], o[k + 1], o[k + 2], o[k + 3]); }
        }
    }
}

__device__ __forceinline__ void done_ticket() {
    unsigned t = atomicAdd(&g_sync[SY_DONE], 1u);
    if (t == 128 * 3 - 1) {
        g_sync[SY_KV] = 0; g_sync[SY_Y] = 0;
        #pragma unroll 1
        for (int i = 0; i < 16; i++) g_sync[SY_O + i] = 0;
        g_sync[SY_EPOCH] = g_sync[SY_EPOCH] + 1;
        g_sync[SY_DONE] = 0;
    }
}
__device__ __forceinline__ uint32_t abuf_off(int c) { return c == 2 ? 0 : (c == 0 || c == 3) ? OFF_S2 : OFF_S3; }
__host__ __device__ constexpr uint32_t wo_ofs(int kb) {
    return kb < 3 ? 32768 + kb * 20480 : kb == 3 ? 0 : kb == 4 ? OFF_S2 : kb == 7 ? OFF_S3 : kb == 9 ? OFF_KVT : kb == 8 ? 32768 + 2 * 20480 : 32768 + (kb - 5) * 20480;
}
__host__ __device__ constexpr uint32_t o_ofs(int k) {
    return k == 6 ? o_ofs(0) : k == 7 ? o_ofs(1) : k == 9 ? o_ofs(2) : k == 0 ? OFF_S2 + 32768 : k == 1 ? OFF_S3 + 32768 : k == 2 ? OFF_OST : k == 3 ? OFF_OST + 8192 : k == 4 ? 20480 : k == 5 ? OFF_S2 + 20480 : OFF_S3 + 20480;
}

__host__ __device__ constexpr uint64_t wo_tab(int a) { uint64_t r = 0; for (int i = 0; i < 5; i++) r |= (uint64_t)(wo_ofs(a + i) >> 10) << (8 * i); return r; }
__host__ __device__ constexpr uint64_t o_tab(int a) { uint64_t r = 0; for (int i = 0; i < 5; i++) r |= (uint64_t)(o_ofs(a + i) >> 10) << (8 * i); return r; }
__device__ __forceinline__ uint32_t wo_off(int kb) { constexpr uint64_t a = wo_tab(0), b = wo_tab(5); return (uint32_t)(((kb < 5 ? a : b) >> (8 * (kb < 5 ? kb : kb - 5))) & 255) << 10; }
__device__ __forceinline__ uint32_t o_off(int kb) { constexpr uint64_t a = o_tab(0), b = o_tab(5); return (uint32_t)(((kb < 5 ? a : b) >> (8 * (kb < 5 ? kb : kb - 5))) & 255) << 10; }
template<int ST> __device__ __forceinline__ void prep_pair(const uint32_t* kw, const uint32_t* vw, const uint4 sk, bf16* dst) {
    const uint32_t w0 = prmt(sk.x, sk.z, 0x5410), w1 = prmt(sk.x, sk.z, 0x7632), w2 = prmt(sk.y, sk.w, 0x5410), w3 = prmt(sk.y, sk.w, 0x7632);
    uint32_t r[8];
    #pragma unroll
    for (int i = 0; i < 8; i++) {
        uint32_t a = hmul2(kw[i * ST], w3);
        a = hfma2(kw[(i + 1) * ST], w2, a); a = hfma2(kw[(i + 2) * ST], w1, a); a = hfma2(kw[(i + 3) * ST], w0, a);
        r[i] = hmul2(a, vw[i * ST]);
    }
    *reinterpret_cast<uint4*>(dst) = make_uint4(prmt(r[7], r[6], 0x5410), prmt(r[5], r[4], 0x5410), prmt(r[3], r[2], 0x5410), prmt(r[1], r[0], 0x5410));
    *reinterpret_cast<uint4*>(dst + 2048) = make_uint4(prmt(r[7], r[6], 0x7632), prmt(r[5], r[4], 0x7632), prmt(r[3], r[2], 0x7632), prmt(r[1], r[0], 0x7632));
}
__device__ __forceinline__ void conv_reduce(uint32_t x, uint32_t y, int warp, int lane) {
    #pragma unroll
    for (int i = 0; i < 2; i++) {
        const uint32_t o = warp * 1024 + i * 512 + lane * 16, xr = x + o;
        const uint4 a0 = lds128(xr), a1 = lds128(xr + 4224 + 32), a2 = lds128(xr + 2 * 4224 + 64), a3 = lds128(xr + 3 * 4224 + 96);
        sts128(y + o, sum4(a0.x, a1.x, a2.x, a3.x), sum4(a0.y, a1.y, a2.y, a3.y), sum4(a0.z, a1.z, a2.z, a3.z), sum4(a0.w, a1.w, a2.w, a3.w));
    }
}
template<int NI> __device__ __forceinline__ void final_items(const Params& P, int bid, int item0) {
    uint4 qv[NI][4];
    #pragma unroll
    for (int n = 0; n < NI; n++) {
        const int item = item0 + n * 128, qd = item & 3, cg = item >> 2;
        #pragma unroll
        for (int r = 0; r < 4; r++) qv[n][r] = ldg_nc(P.q + (size_t)(bid * 16 + (r >> 1 ? 0 : 8) + qd * 2 + (r & 1)) * 640 + cg * 8);
    }
    bar_sync(7, 352);
    uint2 y[NI][8];
    #pragma unroll
    for (int n = 0; n < NI; n++) {
        const int item = item0 + n * 128, qd = item & 3, cg = item >> 2;
        #pragma unroll
        for (int c = 0; c < 8; c++) y[n][c] = ldg_cg2(g_yT + (size_t)(cg * 8 + c) * 1024 + (127 - bid) * 8 + qd * 2);
    }
    #pragma unroll
    for (int n = 0; n < NI; n++) {
        const int item = item0 + n * 128, qd = item & 3, cg = item >> 2;
        #pragma unroll
        for (int r = 0; r < 4; r++) {
            const uint32_t sel = r >> 1 ? 0x7632 : 0x5410;
            uint32_t w[8];
            #pragma unroll
            for (int c = 0; c < 8; c++) w[c] = (r & 1) ? y[n][c].y : y[n][c].x;
            uint4 o;
            o.x = hmul2(qv[n][r].x, prmt(w[0], w[1], sel)); o.y = hmul2(qv[n][r].y, prmt(w[2], w[3], sel));
            o.z = hmul2(qv[n][r].z, prmt(w[4], w[5], sel)); o.w = hmul2(qv[n][r].w, prmt(w[6], w[7], sel));
            *reinterpret_cast<uint4*>(P.out + (size_t)(bid * 16 + (r >> 1 ? 0 : 8) + qd * 2 + (r & 1)) * 1280 + cg * 8) = o;
        }
    }
}

__global__ void __cluster_dims__(2, 1, 1) __launch_bounds__(512, 1)
fused_kernel(const __grid_constant__ CUtensorMap tmX, const __grid_constant__ CUtensorMap tmW64, const __grid_constant__ CUtensorMap tmW16,
             const __grid_constant__ CUtensorMap tmO, const __grid_constant__ CUtensorMap tmWo, const __grid_constant__ CUtensorMap tmOut,
             const __grid_constant__ CUtensorMap tmOst,
             const Params P)
{
    extern __shared__ __align__(1024) uint8_t smem_raw[];
    const uint32_t sb = (uint32_t)__cvta_generic_to_shared(smem_raw);
    const uint32_t bars = sb + OFF_BAR;
    const int tid = threadIdx.x, t = tid & 127, lane = tid & 31;
    const int wg = __shfl_sync(0xffffffff, tid >> 7, 0), warp = __shfl_sync(0xffffffff, t >> 5, 0);
    const int bid = blockIdx.x, rank = bid & 1, hg = (bid >> 1) & 7, rt = (bid >> 4) * 2 + rank;
    const int uid = rt * 8 + hg;
#define BAR(i) (bars + 8 * (i))

    const int c64 = 80 * hg, c16 = 80 * hg + 64;
    if (tid == 0) {
        #pragma unroll
        for (int i = 0; i < 4; i++) mbar_init(BAR(B_EMPTY + i), 16);
        #pragma unroll
        for (int i = B_KV; i < B_OEMPTY; i++) mbar_init(BAR(i), 1);
        asm volatile("fence.mbarrier_init.release.cluster;" ::: "memory");
    }
    if (tid == 32) {
        #pragma unroll
        for (int i = B_OEMPTY; i < NUM_BARS; i++) mbar_init(BAR(i), i == B_KVFREE ? 2 : i == B_QDONE ? 16 : (i < B_AFREE || i >= B_SFREE || (i >= B_AFREE + 2 && i < B_AREADY)) ? 8 : 4);
        asm volatile("fence.mbarrier_init.release.cluster;" ::: "memory");
    }
#define LOAD_X(kb) tma4d(sb + ((kb) & 3) * STAGE_BYTES, &tmX, BAR(B_FULL + ((kb) & 3)), (kb) * 64, rt * 4)
#define LOAD_W(kb) do { tma3d_mc(sb + ((kb) & 3) * STAGE_BYTES + OFF_W64 + rank * 12288, &tmW64, BAR(B_FULL + ((kb) & 3)), c64, (kb) * 64 + rank * 32, 0); \
                        tma3d_mc(sb + ((kb) & 3) * STAGE_BYTES + OFF_W16 + rank * 3072, &tmW16, BAR(B_FULL + ((kb) & 3)), c16, (kb) * 64 + rank * 32, 0); } while (0)
    if (tid == 288) {
        #pragma unroll
        for (int i = 0; i < 4; i++) mbar_init(BAR(B_FULL + i), 1);
        mbar_init(BAR(B_PLOAD), 1);
        asm volatile("fence.mbarrier_init.release.cluster;" ::: "memory");
    }
    __syncwarp();
    asm volatile("barrier.cluster.arrive.relaxed.aligned;" ::: "memory");
    if (tid == 288) {
        #pragma unroll
        for (int i = 0; i < NE; i++) {
            const uint32_t st = sb + i * STAGE_BYTES, fb = BAR(B_FULL + i);
            mbar_expect(fb, STAGE_BYTES);
            LOAD_X(i);
            tma3d(st + OFF_W64, &tmW64, fb, c64, i * 64, 0); tma3d(st + OFF_W64 + 12288, &tmW64, fb, c64, i * 64 + 32, 0);
            tma3d(st + OFF_W16, &tmW16, fb, c16, i * 64, 0); tma3d(st + OFF_W16 + 3072, &tmW16, fb, c16, i * 64 + 32, 0);
        }
        const uint32_t skip = bid == 0 ? 2560 : 0;
        mbar_expect(BAR(B_PLOAD), 23040 + 20480 - skip);
        bulk_load(sb + OFF_KVT + skip, reinterpret_cast<const char*>(P.k) + (size_t)bid * 20480 - 2560 + skip, 23040 - skip, BAR(B_PLOAD));
    }
    if (tid == 416) { prefetch_tm(&tmW64); prefetch_tm(&tmW16); }
    __syncwarp();
#define CL_WAIT() asm volatile("barrier.cluster.wait.aligned;" ::: "memory")

    if (wg == 3) {
        asm volatile("setmaxnreg.dec.sync.aligned.u32 48;");
        CL_WAIT();
        if (warp == 0) {
            if (lane == 0) {
                TR(7);
                #pragma unroll 1
                for (int kb = NE; kb < 10; kb++) {
                    if (kb >= 4) mbar_wait(BAR(B_EMPTY + (kb & 3)), (kb >> 2) - 1);
                    mbar_expect(BAR(B_FULL + (kb & 3)), STAGE_BYTES);
                    LOAD_X(kb); LOAD_W(kb);
                }
                TR(0);
                prefetch_l2(P.wo + (size_t)bid * 3200, 6400);
                prefetch_tm(&tmO); prefetch_tm(&tmWo); prefetch_tm(&tmOut); prefetch_tm(&tmOst);
                const int orow = rt * 128 + (hg & 1) * 64, og = (hg >> 1) * 5;
#define LOAD_WO(kb) tma3d_mc(sb + wo_off(kb) + rank * 10240, &tmWo, BAR(B_OFULL + (kb)), 0, (kb) * 64 + rank * 32, og)
#define LOAD_O(kb) tma2d(sb + o_off(kb), &tmO, BAR(B_OFULL + (kb)), (kb) * 64, orow)
                #pragma unroll 1
                for (int kb = 0; kb < 10; kb++) mbar_expect(BAR(B_OFULL + kb), 28672);
                mbar_wait(BAR(B_ATT), 0);
                tma4d_store(&tmOst, sb + OFF_OST, hg * 80, rt * 4);
                bulk_commit(); bulk_wait0();
                red_relaxed(&g_sync[SY_O + rt], 1);
                TR(1);
                mbar_wait(BAR(B_QDONE), 0);
                #pragma unroll 1
                for (int kb = 0; kb < 3; kb++) LOAD_WO(kb);
                poll_ge(&g_sync[SY_O + rt], 8);
                TR(2);
                prefetch_l2(P.q + (size_t)bid * 10240, 20480);
                #pragma unroll 1
                for (int kb = 0; kb < 4; kb++) LOAD_O(kb);
                mbar_wait(BAR(B_AFREE + 2), 0);
                LOAD_WO(3); LOAD_O(4);
                mbar_wait(BAR(B_AFREE + 3), 0);
                LOAD_WO(4); LOAD_O(5);
                mbar_wait(BAR(B_OEMPTY + 0), 0);
                LOAD_WO(5); LOAD_O(6);
                mbar_wait(BAR(B_OEMPTY + 1), 0);
                LOAD_WO(6); LOAD_O(7);
                mbar_wait(BAR(B_AFREE + 4), 0);
                LOAD_WO(7); LOAD_O(8);
                mbar_wait(BAR(B_OEMPTY + 2), 0);
                LOAD_WO(8); LOAD_O(9);
                mbar_wait(BAR(B_KVFREE), 0);
                LOAD_WO(9);
                done_ticket();
            }
        } else if (warp == 1) {
            if (lane == 0) {
                mbar_wait(BAR(B_PREP), 0);
                red_release(&g_sync[SY_KV], 1);
                TR(9);
                poll_ge(&g_sync[SY_KV], 128);
                TR(3);
                mbar_expect(BAR(B_KV), 5 * 4096);
                #pragma unroll 1
                for (int c = 0; c < 5; c++) bulk_load(sb + OFF_KVT + c * KVT_PITCH, g_kvT + (size_t)(bid * 5 + c) * 2048, 4096, BAR(B_KV));
                done_ticket();
                #pragma unroll 1
                for (int c = 0; c < 5; c++) {
                    mbar_wait(BAR(B_Y + c), 0);
                    bulk_store(g_yT + (size_t)(bid * 5 + c) * 1024, sb + OFF_KVT + c * KVT_PITCH, 4096);
                    bulk_commit(); bulk_wait0();
                    red_relaxed(&g_sync[SY_Y], 1);
                }
                mbar_arrive_remote(BAR(B_KVFREE), 0); mbar_arrive_remote(BAR(B_KVFREE), 1);
                TR(4);
                poll_ge(&g_sync[SY_Y], 640);
            }
            __syncwarp();
            bar_arrive(7, 352);
            if (lane == 0) done_ticket();
        } else {
            mbar_wait(BAR(B_AREADY + 4), 0);
            final_items<1>(P, bid, 256 + (t - 64));
        }
    } else if (wg == 2) {
        {
            const int hf = (lane >> 3) & 1, ch = ((lane & 7) + (lane >> 4) * 8 + warp * 16) * 8;
            const int hf2 = lane >> 4, ch2 = 512 + warp * 32 + (lane & 15) * 2;
            const bf16* krow = P.k + (size_t)(bid ? bid * 16 - 3 : 0) * 640;
            uint4 skv[4];
            #pragma unroll
            for (int cp = 0; cp < 4; cp++) skv[cp] = ldg_ca(P.shift_k + (ch + cp * 2) * 4);
            const uint4 k3 = ldg_ca(krow + ch), sk2 = ldg_ca(P.shift_k + ch2 * 4);
            const uint32_t k32 = *reinterpret_cast<const uint32_t*>(krow + ch2);
            CL_WAIT();
            if (t == 0) {
                if (VW >= 0) mbar_wait(BAR(B_FULL + VW), 0);
                bulk_load(sb + OFF_PV, P.v + (size_t)bid * 10240, 20480, BAR(B_PLOAD));
            }
            __syncwarp();
            mbar_wait(BAR(B_PLOAD), 0);
            TRT(17);
            uint4 kr[11], vr[8];
            uint32_t k2[11], v2[8];
            #pragma unroll
            for (int i = 0; i < 11; i++) kr[i] = lds128(sb + OFF_KVT + (hf * 8 + i - (i || hf ? 1 : 0)) * 1280 + ch * 2);
            #pragma unroll
            for (int i = 0; i < 8; i++) vr[i] = lds128(sb + OFF_PV + (hf * 8 + i) * 1280 + ch * 2);
            if (!hf) kr[0] = k3;
            if (!hf && !bid) { kr[0] = kr[1] = kr[2] = make_uint4(0, 0, 0, 0); }
            bf16* dst = g_kvT + (size_t)ch * 2048 + (2040 - bid * 16 - hf * 8);
            #pragma unroll
            for (int cp = 0; cp < 4; cp++) prep_pair<4>(reinterpret_cast<const uint32_t*>(kr) + cp, reinterpret_cast<const uint32_t*>(vr) + cp, skv[cp], dst + cp * 4096);
            #pragma unroll
            for (int i = 0; i < 11; i++) k2[i] = lds32(sb + OFF_KVT + (hf2 * 8 + i - (i || hf2 ? 1 : 0)) * 1280 + ch2 * 2);
            #pragma unroll
            for (int i = 0; i < 8; i++) v2[i] = lds32(sb + OFF_PV + (hf2 * 8 + i) * 1280 + ch2 * 2);
            if (!hf2) k2[0] = k32;
            if (!hf2 && !bid) { k2[0] = k2[1] = k2[2] = 0; }
            prep_pair<1>(k2, v2, sk2, g_kvT + (size_t)ch2 * 2048 + (2040 - bid * 16 - hf2 * 8));
        }
        __syncwarp();
        if (lane == 0) mbar_arrive(BAR(B_PREP));
        bar_sync(4, 128);
        if (t < 10) {
            sts128(sb + OFF_KVT + (t >> 1) * KVT_PITCH + 4096 + (t & 1) * 16, 0, 0, 0, 0);
        }
        TRT(8);
        HRegs hr, h1, h2, h3, h4;
        mbar_wait(BAR(B_FULL + HW), 1);
        h_load(hr, P, bid * 5, t); h_load(h1, P, bid * 5 + 1, t); h_load(h2, P, bid * 5 + 2, t); h_load(h3, P, bid * 5 + 3, t); h_load(h4, P, bid * 5 + 4, t);
        #pragma unroll 1
        for (int c = 0; c < 5; c++) {
            if (c < 2) mbar_wait(BAR(B_SFREE + c), 0);
            else if (c == 2) mbar_wait(BAR(B_QDONE), 0);
            else mbar_wait(BAR(B_AFREE + c - 3), 0);
            if (c == 4) { conv_reduce(sb + OFF_S3, sb + OFF_KVT + KVT_PITCH, warp, lane); bar_sync(4, 128); }
            h_expand(hr, sb + abuf_off(c), t);
            fence_async_smem(); __syncwarp();
            if (lane == 0) { mbar_arrive(BAR(B_AREADY + c)); if (c == 4) mbar_arrive(BAR(B_Y + 1)); }
            TRT(10 + c);
            hr = h1; h1 = h2; h2 = h3; h3 = h4;
        }
        final_items<1>(P, bid, t);
        TRT(19);
    } else {
        asm volatile("setmaxnreg.inc.sync.aligned.u32 168;");
        CL_WAIT();
        if (tid == 0) TR(6);
        const int g = lane >> 2, tq = lane & 3;
        {
            float d[96], d2[24];
            const uint32_t arow = wg * 8192 + (warp * 16 + (lane & 15)) * 128;
            const unsigned epoch = ld_relaxed(&g_sync[SY_EPOCH]) + 1;
#define QKV_LOAD(af, st, h) do { \
                ldsm4(af, (st) + arow + (((4 * (h) + (lane >> 4)) ^ (lane & 7)) << 4)); ldsm4(af + 4, (st) + arow + (((4 * (h) + 2 + (lane >> 4)) ^ (lane & 7)) << 4)); } while (0)
#define QKV_MMA(af, st, h, acc) do { \
                const uint64_t db = mkdesc((st) + OFF_W64 + (h) * 12288, 4096, 1024, 1), dc = mkdesc((st) + OFF_W16 + (h) * 3072, 1024, 256, 3); \
                WG_FENCE(); \
                wgmma_rs<192>(d, af, db, acc); wgmma_rs<48>(d2, af, dc, acc); \
                wgmma_rs<192>(d, af + 4, db + 128, 1); wgmma_rs<48>(d2, af + 4, dc + 32, 1); \
                WG_COMMIT(); \
                WG_WAIT(1); } while (0)
            uint32_t afa[8], afb[8];
            #pragma unroll 1
            for (int kb = 0; kb < 10; kb++) {
                const uint32_t st = sb + (kb & 3) * STAGE_BYTES;
                mbar_wait(BAR(B_FULL + (kb & 3)), (kb >> 2) & 1);
                if (wg == 0) TRT(20 + kb);
                QKV_LOAD(afa, st, 0);
                QKV_MMA(afa, st, 0, kb != 0);
                if (kb < 7) { if (kb > 0 && lane < 2) mbar_arrive_remote(BAR(B_EMPTY + ((kb - 1) & 3)), lane); }
                else if (kb < 9 && lane == 0) mbar_arrive(BAR(B_SFREE + kb - 7));
                QKV_LOAD(afb, st, 1);
                QKV_MMA(afb, st, 1, 1);
            }
            WG_WAIT(0);
            if (lane < 2) mbar_arrive_remote(BAR(B_QDONE), lane);
            if (wg == 0) TRT(30);
            uint32_t Ql[10], Qh[10], Kl[10], Kh[10], Vl[10], Vh[10], Kp[10], Vp[10];
            #pragma unroll
            for (int b = 0; b < 10; b++) {
                const float* xk = b < 8 ? d + 32 + 4 * b : d2 + 8 + 4 * (b - 8);
                const float* xv = b < 8 ? d + 64 + 4 * b : d2 + 16 + 4 * (b - 8);
                Kh[b] = pack_bf16(xk[2], xk[3]);
                Vh[b] = movm(pack_bf16(xv[2], xv[3]));
            }
            const int G = wg * 4 + warp;
            if (G < 6) {
                mbar_wait(BAR(B_SFREE + wg), 0);
                const uint32_t xa = sb + ((G & 4) ? OFF_S3 : OFF_S2) + 32768 + (G & 3) * 2560 + lane * 16;
                sts128(xa, Kh[0], Kh[1], Kh[2], Kh[3]); sts128(xa + 512, Kh[4], Kh[5], Kh[6], Kh[7]); sts128(xa + 1024, Kh[8], Kh[9], Vh[0], Vh[1]);
                sts128(xa + 1536, Vh[2], Vh[3], Vh[4], Vh[5]); sts128(xa + 2048, Vh[6], Vh[7], Vh[8], Vh[9]);
            } else if (rt < 15) {
                uint4* gp = g_halo + (size_t)(uid * 2 + (G & 1)) * 224 + lane;
                st_relaxed4(gp, Kh[0], Kh[1], Kh[2], epoch); st_relaxed4(gp + 32, Kh[3], Kh[4], Kh[5], epoch); st_relaxed4(gp + 64, Kh[6], Kh[7], Kh[8], epoch);
                st_relaxed4(gp + 96, Kh[9], Vh[0], Vh[1], epoch); st_relaxed4(gp + 128, Vh[2], Vh[3], Vh[4], epoch); st_relaxed4(gp + 160, Vh[5], Vh[6], Vh[7], epoch);
                st_relaxed4(gp + 192, Vh[8], Vh[9], 0, epoch);
            }
            #pragma unroll
            for (int b = 0; b < 10; b++) {
                const float* xq = b < 8 ? d + 4 * b : d2 + 4 * (b - 8);
                const float* xk = b < 8 ? d + 32 + 4 * b : d2 + 8 + 4 * (b - 8);
                const float* xv = b < 8 ? d + 64 + 4 * b : d2 + 16 + 4 * (b - 8);
                Ql[b] = pack_bf16(xq[0], xq[1]); Qh[b] = pack_bf16(xq[2], xq[3]);
                Kl[b] = pack_bf16(xk[0], xk[1]);
                Vl[b] = movm(pack_bf16(xv[0], xv[1]));
            }
            float S0[4][4], S1[4][4], Sp[4][4];
            #pragma unroll
            for (int h = 0; h < 4; h++) {
                const int f0 = (h >> 1) * 5 + (h & 1) * 3, sk = (h >> 1) * 5 + 2;
                const bool hm = (h & 1) ? (tq >= 2) : (tq < 2);
                const uint32_t al = hm ? Ql[sk] : 0u, ah = hm ? Qh[sk] : 0u;
                #pragma unroll
                for (int i = 0; i < 4; i++) { S0[h][i] = 0.f; S1[h][i] = 0.f; Sp[h][i] = 0.f; }
                mma16(S0[h], Ql[f0], Qh[f0], Ql[f0 + 1], Qh[f0 + 1], Kl[f0], Kl[f0 + 1]); mma8(S0[h], al, ah, Kl[sk]);
                mma16(S1[h], Ql[f0], Qh[f0], Ql[f0 + 1], Qh[f0 + 1], Kh[f0], Kh[f0 + 1]); mma8(S1[h], al, ah, Kh[sk]);
            }
            bar_sync(1, 256);
            if (G >= 2) {
                const int Gs = G - 2;
                const uint32_t xa = sb + ((Gs & 4) ? OFF_S3 : OFF_S2) + 32768 + (Gs & 3) * 2560 + lane * 16;
                uint4 a = lds128(xa), b = lds128(xa + 512), c = lds128(xa + 1024), e = lds128(xa + 1536), f = lds128(xa + 2048);
                Kp[0] = a.x; Kp[1] = a.y; Kp[2] = a.z; Kp[3] = a.w; Kp[4] = b.x; Kp[5] = b.y; Kp[6] = b.z; Kp[7] = b.w; Kp[8] = c.x; Kp[9] = c.y;
                Vp[0] = c.z; Vp[1] = c.w; Vp[2] = e.x; Vp[3] = e.y; Vp[4] = e.z; Vp[5] = e.w; Vp[6] = f.x; Vp[7] = f.y; Vp[8] = f.z; Vp[9] = f.w;
            } else if (rt > 0) {
                const uint4* gp = g_halo + (size_t)((uid - 8) * 2 + G) * 224 + lane;
                uint4 u[7];
                int it = 0;
                #pragma unroll 1
                for (;; it++) {
                    #pragma unroll
                    for (int i = 0; i < 7; i++) u[i] = ld_relaxed4(gp + 32 * i);
                    bool ok = true;
                    #pragma unroll
                    for (int i = 0; i < 7; i++) ok = ok && (u[i].w == epoch);
                    if (__all_sync(0xffffffff, ok)) break;
                    if (it > (1 << 20)) __trap();
                }
                Kp[0] = u[0].x; Kp[1] = u[0].y; Kp[2] = u[0].z; Kp[3] = u[1].x; Kp[4] = u[1].y; Kp[5] = u[1].z; Kp[6] = u[2].x; Kp[7] = u[2].y; Kp[8] = u[2].z; Kp[9] = u[3].x;
                Vp[0] = u[3].y; Vp[1] = u[3].z; Vp[2] = u[4].x; Vp[3] = u[4].y; Vp[4] = u[4].z; Vp[5] = u[5].x; Vp[6] = u[5].y; Vp[7] = u[5].z; Vp[8] = u[6].x; Vp[9] = u[6].y;
            } else {
                #pragma unroll
                for (int b = 0; b < 10; b++) { Kp[b] = 0; Vp[b] = 0; }
            }
            if (G == 0) TRT(5);
            const bool noprev = (G < 2) && (rt == 0);
            const bool up0 = 2 * tq > g, up1 = 2 * tq + 1 > g;
            const float sc = 0.22360679774997896f * 1.4426950408889634f, NEG = -1.4426950408889634e9f;
            uint32_t Ol[10], Oh[10];
            float Os[4];
            #pragma unroll
            for (int h = 0; h < 4; h++) {
                const int f0 = (h >> 1) * 5 + (h & 1) * 3, sk = (h >> 1) * 5 + 2;
                const bool hm = (h & 1) ? (tq >= 2) : (tq < 2);
                const uint32_t al = hm ? Ql[sk] : 0u, ah = hm ? Qh[sk] : 0u;
                mma16(Sp[h], Ql[f0], Qh[f0], Ql[f0 + 1], Qh[f0 + 1], Kp[f0], Kp[f0 + 1]); mma8(Sp[h], al, ah, Kp[sk]);
                float a0 = up0 ? (noprev ? NEG : Sp[h][0] * sc) : S0[h][0] * sc, a1 = up1 ? (noprev ? NEG : Sp[h][1] * sc) : S0[h][1] * sc;
                float b0 = (up0 ? S0[h][2] : S1[h][2]) * sc, b1 = (up1 ? S0[h][3] : S1[h][3]) * sc;
                float ma = fmaxf(a0, a1), mb = fmaxf(b0, b1);
                ma = fmaxf(ma, __shfl_xor_sync(0xffffffff, ma, 1)); mb = fmaxf(mb, __shfl_xor_sync(0xffffffff, mb, 1));
                ma = fmaxf(ma, __shfl_xor_sync(0xffffffff, ma, 2)); mb = fmaxf(mb, __shfl_xor_sync(0xffffffff, mb, 2));
                a0 = ex2(a0 - ma); a1 = ex2(a1 - ma); b0 = ex2(b0 - mb); b1 = ex2(b1 - mb);
                float sa = a0 + a1, sbm = b0 + b1;
                sa += __shfl_xor_sync(0xffffffff, sa, 1); sbm += __shfl_xor_sync(0xffffffff, sbm, 1);
                sa += __shfl_xor_sync(0xffffffff, sa, 2); sbm += __shfl_xor_sync(0xffffffff, sbm, 2);
                const float ia = rcp(sa), ib = rcp(sbm);
                a0 *= ia; a1 *= ia; b0 *= ib; b1 *= ib;
                const uint32_t Pp = pack_bf16(up0 ? a0 : 0.f, up1 ? a1 : 0.f), P0l = pack_bf16(up0 ? 0.f : a0, up1 ? 0.f : a1);
                const uint32_t P0h = pack_bf16(up0 ? b0 : 0.f, up1 ? b1 : 0.f), P1h = pack_bf16(up0 ? 0.f : b0, up1 ? 0.f : b1);
                #pragma unroll
                for (int n = 0; n < 3; n++) {
                    const int b = n < 2 ? f0 + n : sk;
                    float o[4] = {0.f, 0.f, 0.f, 0.f};
                    mma16(o, P0l, P0h, 0u, P1h, Vl[b], Vh[b]); mma8(o, Pp, 0u, Vp[b]);
                    if (n < 2) { Ol[b] = pack_bf16(o[0], o[1]); Oh[b] = pack_bf16(o[2], o[3]); }
                    else if ((h & 1) == 0) { Os[0] = o[0]; Os[1] = o[1]; Os[2] = o[2]; Os[3] = o[3]; }
                    else { Ol[b] = hm ? pack_bf16(o[0], o[1]) : pack_bf16(Os[0], Os[1]); Oh[b] = hm ? pack_bf16(o[2], o[3]) : pack_bf16(Os[2], Os[3]); }
                }
            }
            mbar_wait(BAR(B_PREP), 0);
            const int mi = lane >> 3;
            const uint32_t rowa = sb + OFF_OST + (G * 16 + (mi & 1) * 8 + (lane & 7)) * 160 + (mi >> 1) * 16;
            #pragma unroll
            for (int b = 0; b < 10; b += 2) stsm4(rowa + b * 16, Ol[b], Oh[b], Ol[b + 1], Oh[b + 1]);
            fence_async_smem();
            __syncwarp();
            if (lane == 0) mbar_arrive(BAR(B_ATT));
            TRT(15 + wg);
        }
        {
            mbar_wait(BAR(B_KV), 0);
            const uint32_t lane_off = tq * 32 + g * 4;
            #pragma unroll 1
            for (int c = wg ^ 1; c < 5; c += 2) {
                const uint32_t abuf = sb + abuf_off(c);
                const uint64_t da = mkdesc(abuf, 16, 1024, 1);
                mbar_wait(BAR(B_AREADY + c), 0);
                float lo[96], hi[32];
                const uint64_t db = mkdesc(sb + OFF_KVT + c * KVT_PITCH, 16, 128, 0);
                if (c > 0) bar_sync(5 + wg, 256);
                TRT(32 + c);
                WG_FENCE();
                conv_steps<0>(lo, hi, da, db); conv_steps<1>(lo, hi, da, db); conv_steps<2>(lo, hi, da, db); conv_steps<3>(lo, hi, da, db);
                conv_steps<4>(lo, hi, da, db); conv_steps<5>(lo, hi, da, db); conv_steps<6>(lo, hi, da, db); conv_steps<7>(lo, hi, da, db);
                conv_steps<8>(lo, hi, da, db); conv_steps<9>(lo, hi, da, db); conv_steps<10>(lo, hi, da, db); conv_steps<11>(lo, hi, da, db);
                WG_COMMIT();
                conv_steps<12>(lo, hi, da, db); conv_steps<13>(lo, hi, da, db); conv_steps<14>(lo, hi, da, db); conv_steps<15>(lo, hi, da, db);
                WG_COMMIT();
                WG_WAIT(1);
                bar_arrive(5 + (wg ^ 1), 256);
                WG_WAIT(0);
                TRT(37 + c);
                #pragma unroll
                for (int j = 0; j < 23; j++) { lo[4 * j] += lo[4 * j + 6]; lo[4 * j + 1] += lo[4 * j + 7]; }
                lo[92] += hi[2]; lo[93] += hi[3];
                #pragma unroll
                for (int j = 0; j < 7; j++) { hi[4 * j] += hi[4 * j + 6]; hi[4 * j + 1] += hi[4 * j + 7]; }
                bar_sync(2 + wg, 128);
                const uint32_t xw = abuf + warp * 4224 + lane_off;
                #pragma unroll
                for (int j = 0; j < 24; j++) sts32(xw + j * 128, pack_bf16(lo[4 * j], lo[4 * j + 1]));
                #pragma unroll
                for (int j = 0; j < 8; j++) sts32(xw + 3072 + j * 128, pack_bf16(hi[4 * j], hi[4 * j + 1]));
                sts32(xw + 4096, 0);
                if (c == 1) {
                    __syncwarp();
                    if (lane == 0) mbar_arrive(BAR(B_AFREE + 1));
                } else {
                    bar_sync(2 + wg, 128);
                    conv_reduce(abuf, sb + OFF_KVT + c * KVT_PITCH, warp, lane);
                    fence_async_smem();
                    __syncwarp();
                    if (lane == 0) { mbar_arrive(BAR(B_Y + c)); mbar_arrive(BAR(B_AFREE + c)); }
                    if (lane == 1 && c >= 2) mbar_arrive_remote(BAR(B_AFREE + c), rank ^ 1);
                }
                TRT(42 + c);
            }
            if (wg == 0) bar_sync(5, 256);
        }
        if (wg == 0) {
            float d[80];
            #pragma unroll 1
            for (int kb = 0; kb < 10; kb++) {
                mbar_wait(BAR(B_OFULL + kb), 0);
                TRT(47 + kb);
                const uint64_t da = mkdesc(sb + o_off(kb), 16, 1024, 1);
                const uint64_t db = mkdesc(sb + wo_off(kb), 2048, 512, 2);
                WG_FENCE();
                #pragma unroll
                for (int k = 0; k < 4; k++) wgmma_ss<160, 1>(d, da + k * 2, db + (k >> 1) * 640 + (k & 1) * 64, (kb | k) != 0);
                WG_COMMIT();
                if (kb >= 1 && kb <= 3) { WG_WAIT(1); if (lane < 2) mbar_arrive_remote(BAR(B_OEMPTY + kb - 1), lane); }
            }
            WG_WAIT(0);
            TRT(57);
            bar_sync(2, 128);
            const int mi = lane >> 3, r = (lane & 7) + 8 * (mi & 1);
            const uint32_t stg = sb + warp * 5120;
            #pragma unroll
            for (int b = 0; b < 5; b++) {
                #pragma unroll
                for (int hh = 0; hh < 2; hh++) {
                    const float* x = d + b * 16 + hh * 8;
                    const uint32_t chunk = (hh * 2 + (mi >> 1)) ^ ((r >> 1) & 3);
                    stsm4(stg + b * 1024 + r * 64 + chunk * 16, pack_bf16(x[0], x[1]), pack_bf16(x[2], x[3]), pack_bf16(x[4], x[5]), pack_bf16(x[6], x[7]));
                }
            }
            fence_async_smem();
            __syncwarp();
            if (lane == 0) {
                tma3d_store(&tmOut, stg, rt * 128 + (hg & 1) * 64 + warp * 16, 20 + (hg >> 1) * 5);
                bulk_commit(); bulk_wait0_read();
                if (warp == 0) TR(59);
            }
        } else {
            final_items<1>(P, bid, 128 + t);
        }
    }
}

typedef CUresult (*EncFn)(CUtensorMap*, CUtensorMapDataType, cuuint32_t, void*, const cuuint64_t*, const cuuint64_t*, const cuuint32_t*, const cuuint32_t*,
                          CUtensorMapInterleave, CUtensorMapSwizzle, CUtensorMapL2promotion, CUtensorMapFloatOOBfill);

static void enc_map(EncFn enc, CUtensorMap* tm, void* ptr, int rank, const cuuint64_t* gd, const cuuint64_t* gs, const cuuint32_t* box, CUtensorMapSwizzle sw) {
    cuuint32_t es[4] = {1, 1, 1, 1};
    enc(tm, CU_TENSOR_MAP_DATA_TYPE_BFLOAT16, rank, ptr, gd, gs, box, es, CU_TENSOR_MAP_INTERLEAVE_NONE, sw, CU_TENSOR_MAP_L2_PROMOTION_L2_128B, CU_TENSOR_MAP_FLOAT_OOB_FILL_NONE);
}

extern "C" void kernel_launch(void* const* d_in, const int* in_sizes, int n_in, void* d_out, int out_size) {
    static EncFn enc = nullptr;
    static void* o_ptr = nullptr;
    if (!enc) {
        void* fn = nullptr; cudaDriverEntryPointQueryResult qr;
        cudaGetDriverEntryPoint("cuTensorMapEncodeTiled", &fn, cudaEnableDefault, &qr);
        enc = (EncFn)fn;
        cudaGetSymbolAddress(&o_ptr, g_o);
        cudaFuncSetAttribute(fused_kernel, cudaFuncAttributeMaxDynamicSharedMemorySize, SMEM_BYTES);
    }
    CUtensorMap tmX, tmW64, tmW16, tmO, tmWo, tmOut, tmOst;
    { cuuint64_t gd[4] = {640, 16, 2, 64}, gs[3] = {2560, 1280, 40960}; cuuint32_t box[4] = {64, 16, 2, 4}; enc_map(enc, &tmX, d_in[6], 4, gd, gs, box, CU_TENSOR_MAP_SWIZZLE_128B); }
    { cuuint64_t gd[4] = {640, 16, 2, 64}, gs[3] = {2560, 1280, 40960}; cuuint32_t box[4] = {80, 16, 2, 4}; enc_map(enc, &tmOst, o_ptr, 4, gd, gs, box, CU_TENSOR_MAP_SWIZZLE_NONE); }
    { cuuint64_t gd[3] = {640, 640, 3}, gs[2] = {3840, 1280}; cuuint32_t box[3] = {64, 32, 3}; enc_map(enc, &tmW64, d_in[7], 3, gd, gs, box, CU_TENSOR_MAP_SWIZZLE_128B); }
    { cuuint64_t gd[3] = {640, 640, 3}, gs[2] = {3840, 1280}; cuuint32_t box[3] = {16, 32, 3}; enc_map(enc, &tmW16, d_in[7], 3, gd, gs, box, CU_TENSOR_MAP_SWIZZLE_32B); }
    { cuuint64_t gd[2] = {640, 2048}, gs[1] = {1280}; cuuint32_t box[2] = {64, 64}; enc_map(enc, &tmO, o_ptr, 2, gd, gs, box, CU_TENSOR_MAP_SWIZZLE_128B); }
    { cuuint64_t gd[3] = {32, 640, 20}, gs[2] = {1280, 64}; cuuint32_t box[3] = {32, 32, 5}; enc_map(enc, &tmWo, d_in[8], 3, gd, gs, box, CU_TENSOR_MAP_SWIZZLE_64B); }
    { cuuint64_t gd[3] = {32, 2048, 40}, gs[2] = {2560, 64}; cuuint32_t box[3] = {32, 16, 5}; enc_map(enc, &tmOut, d_out, 3, gd, gs, box, CU_TENSOR_MAP_SWIZZLE_64B); }
    Params P;
    P.q = (const bf16*)d_in[0]; P.k = (const bf16*)d_in[1]; P.v = (const bf16*)d_in[2];
    P.shift_k = (const bf16*)d_in[3]; P.ssm_k = (const bf16*)d_in[4]; P.ssm_D = (const bf16*)d_in[5];
    P.out = (bf16*)d_out; P.x = (const bf16*)d_in[6]; P.wqkv = (const bf16*)d_in[7]; P.wo = (const bf16*)d_in[8];
    fused_kernel<<<128, 512, SMEM_BYTES>>>(tmX, tmW64, tmW16, tmO, tmWo, tmOut, tmOst, P);
}
```
